```python
import torch

def _softmax(x, axis=-1):
    return torch.softmax(x, dim=axis)

def _gelu(x):
    return torch.nn.functional.gelu(x, approximate='tanh')

def _silu(x):
    return torch.nn.functional.silu(x)

def _sigmoid(x):
    return torch.sigmoid(x)

def _layernorm(x, axis=-1, eps=1e-05):
    m = x.mean(dim=axis, keepdim=True)
    v = x.var(dim=axis, keepdim=True, unbiased=False)
    return (x - m) / torch.sqrt(v + eps)

def _scatter_add(tgt, idx, src, axis=0):
    return tgt.clone().index_add_(axis, idx, src)

def _segment_sum(src, seg, n):
    out = torch.zeros((n,) + src.shape[1:], dtype=src.dtype)
    return out.index_add_(0, seg, src)

def _pad(x, pw):
    flat = tuple((v for pair in reversed(pw) for v in pair))
    return torch.nn.functional.pad(x, flat)
kernel_name = 'concat_heads__ssm_conv_s4d__memory_aug_recurrent_mem_tr__prompt'

def setup_inputs():

    _w = lambda a: (lambda t: t.to(torch.bfloat16) if t.is_floating_point() else t)(torch.as_tensor(a))

    def _A_setup():
        Bsz, L, D, N = (1, 2048, 448, 256)
        return {'u': _w((lambda *s: torch.randn(*s, dtype=torch.bfloat16) * 0.05)(Bsz, L, D)), 'log_A_real': _w((lambda *s: torch.randn(*s, dtype=torch.bfloat16) * 6.4)(D, N) * 0.5), 'A_imag': _w((lambda *s: torch.randn(*s, dtype=torch.bfloat16) * 0.05)(D, N) * 3.14), 'C_real': _w((lambda *s: torch.randn(*s, dtype=torch.bfloat16) * 0.2)(D, N) / N ** 0.5), 'C_imag': _w((lambda *s: torch.randn(*s, dtype=torch.bfloat16) * 0.2)(D, N) / N ** 0.5), 'log_dt': _w((lambda *s: torch.randn(*s, dtype=torch.bfloat16) * 0.05)(D) * 0.5 - 4.0), 'D_skip': _w((lambda *s: torch.randn(*s, dtype=torch.bfloat16) * 0.05)(D))}
    _A_in = _A_setup()

    def _B_setup():
        B, S, Dm = (1, 2048, 448)
        H, Dh = (16, 256)
        M, seg = (8, 32)
        seg = min(seg, S)
        S = S // seg * seg
        return {'x': _w((lambda *s: torch.randn(*s, dtype=torch.bfloat16) * 0.05)(B, S, Dm)), 'mem0': _w((lambda *s: torch.randn(*s, dtype=torch.bfloat16) * 0.4)(B, M, Dm)), 'Wq': _w((lambda *s: torch.randn(*s, dtype=torch.bfloat16) * 6.4)(Dm, H, Dh) * Dm ** (-0.5)), 'Wk': _w((lambda *s: torch.randn(*s, dtype=torch.bfloat16) * 6.4)(Dm, H, Dh) * Dm ** (-0.5)), 'Wv': _w((lambda *s: torch.randn(*s, dtype=torch.bfloat16) * 0.4)(Dm, H, Dh) * Dm ** (-0.5)), 'Wo': _w((lambda *s: torch.randn(*s, dtype=torch.bfloat16) * 0.4)(H, Dh, Dm) * (H * Dh) ** (-0.5)), 'seg_len': seg}
    _B_in = _B_setup()
    return {'A_u': _A_in['u'], 'A_log_A_real': _A_in['log_A_real'], 'A_A_imag': _A_in['A_imag'], 'A_C_real': _A_in['C_real'], 'A_C_imag': _A_in['C_imag'], 'A_log_dt': _A_in['log_dt'], 'A_D_skip': _A_in['D_skip'], 'B_x': _B_in['x'], 'B_mem0': _B_in['mem0'], 'B_Wq': _B_in['Wq'], 'B_Wk': _B_in['Wk'], 'B_Wv': _B_in['Wv'], 'B_Wo': _B_in['Wo'], 'B_seg_len': _B_in['seg_len']}

def reference(A_u, A_log_A_real, A_A_imag, A_C_real, A_C_imag, A_log_dt, A_D_skip, B_x, B_mem0, B_Wq, B_Wk, B_Wv, B_Wo, B_seg_len):

    def _A_ref(u, log_A_real, A_imag, C_real, C_imag, log_dt, D_skip):
        L = u.shape[1]
        dt = torch.exp(log_dt)
        A = -torch.exp(log_A_real) + 1j * A_imag
        C = (C_real + 1j * C_imag) * dt[:, None]
        pos = (lambda x, dt: x.to(dt))(torch.arange(L), log_dt.dtype)
        P = torch.exp((A * dt[:, None])[:, :, None] * pos[None, None, :])
        K = 2.0 * torch.einsum('dn,dnl->dl', C, P).real
        L2 = 2 * L
        u_t = (lambda x, *d: x.permute(*d))(u, 0, 2, 1)
        Kf = (lambda x, *a, **k: torch.fft.rfft(x.float(), *a, **k))(K, L2)
        Uf = (lambda x, *a, **k: torch.fft.rfft(x.float(), *a, **k))(u_t, L2)
        y = (lambda x, *a, **k: torch.fft.irfft(x, *a, **k).to(torch.bfloat16))(Uf * Kf[None, :, :], L2)[:, :, :L]
        y = (lambda x, *d: x.permute(*d))(y, 0, 2, 1)
        return y + u * D_skip[None, None, :]

    def _B_ref(x, mem0, Wq, Wk, Wv, Wo, seg_len):
        B, S, Dm = x.shape
        H, Dh = (Wq.shape[1], Wq.shape[2])
        M = mem0.shape[1]
        scale = Dh ** (-0.5)
        n_seg = S // seg_len
        L = M + seg_len
        idx = torch.arange(L)
        mask = (idx[:, None] < M) | (idx[:, None] >= idx[None, :])
        mem = mem0
        outs = []
        for s in range(n_seg):
            xs = x[:, s * seg_len:(s + 1) * seg_len, :].clone()
            h = torch.concatenate([mem, xs], axis=1)
            q = torch.einsum('btd,dhe->bhte', h, Wq)
            k = torch.einsum('btd,dhe->bhte', h, Wk)
            v = torch.einsum('btd,dhe->bhte', h, Wv)
            scores = torch.einsum('bhqe,bhke->bhqk', q, k) * scale
            scores = torch.where(mask[None, None], scores, -1000000000.0)
            p = _softmax(scores, axis=-1)
            o = torch.einsum('bhqk,bhke->bhqe', p, v)
            o = torch.einsum('bhte,hed->btd', o, Wo)
            mem = o[:, :M, :].clone()
            outs.append(o[:, M:, :])
        return torch.concatenate(outs, axis=1)
    a = _A_ref(A_u, A_log_A_real, A_A_imag, A_C_real, A_C_imag, A_log_dt, A_D_skip)
    b = _B_ref(B_x, B_mem0, B_Wq, B_Wk, B_Wv, B_Wo, B_seg_len)
    return torch.concatenate([a, b], axis=-1)
```

```cpp
#include <cuda.h>
#include <cuda_runtime.h>
#include <cuda_bf16.h>
#include <stdint.h>
#include <string.h>

namespace {

constexpr int D = 448, S = 2048, NSEG = 64, OUTW = 896, NST8 = 256;
#define RING 16
constexpr int RECC = 16384, RECB = 4 * RECC;
__device__ __align__(1024) uint8_t g_REC[(size_t)RING * 16 * RECB];
__device__ __align__(16384) uint8_t g_ACC[33 * 16384];
__device__ uint4 g_XA[128 * 28 * 32];
constexpr int F_ZERO = 128, F_PROG = 129, F_WORK = 130, F_DONE = 131;
__device__ int g_FLAG[132 * 32];
#define GT(k, i)
#define GF(k, i)

__device__ __forceinline__ uint32_t smem_u32(const void* p) { return (uint32_t)__cvta_generic_to_shared(p); }
__device__ __forceinline__ void mma(float* c, const uint4& a, uint32_t b0, uint32_t b1) {
    asm volatile("mma.sync.aligned.m16n8k16.row.col.f32.bf16.bf16.f32 {%0,%1,%2,%3},{%4,%5,%6,%7},{%8,%9},{%0,%1,%2,%3};"
                 : "+f"(c[0]), "+f"(c[1]), "+f"(c[2]), "+f"(c[3]) : "r"(a.x), "r"(a.y), "r"(a.z), "r"(a.w), "r"(b0), "r"(b1));
}
__device__ __forceinline__ void mmaz(float* c, const uint4& a, uint32_t b0, uint32_t b1) {
    asm volatile("mma.sync.aligned.m16n8k16.row.col.f32.bf16.bf16.f32 {%0,%1,%2,%3},{%4,%5,%6,%7},{%8,%9},{%10,%10,%10,%10};"
                 : "=f"(c[0]), "=f"(c[1]), "=f"(c[2]), "=f"(c[3]) : "r"(a.x), "r"(a.y), "r"(a.z), "r"(a.w), "r"(b0), "r"(b1), "f"(0.f));
}
__device__ __forceinline__ void mma8(float* c, uint32_t a0, uint32_t a1, uint32_t b0) {
    asm volatile("mma.sync.aligned.m16n8k8.row.col.f32.bf16.bf16.f32 {%0,%1,%2,%3},{%4,%5},{%6},{%0,%1,%2,%3};"
                 : "+f"(c[0]), "+f"(c[1]), "+f"(c[2]), "+f"(c[3]) : "r"(a0), "r"(a1), "r"(b0));
}
__device__ __forceinline__ uint32_t pack(float lo, float hi) { uint32_t r; asm("cvt.rn.bf16x2.f32 %0,%1,%2;" : "=r"(r) : "f"(hi), "f"(lo)); return r; }
__device__ __forceinline__ uint32_t movm(uint32_t a) { uint32_t d; asm volatile("movmatrix.sync.aligned.m8n8.trans.b16 %0,%1;" : "=r"(d) : "r"(a)); return d; }
__device__ __forceinline__ uint4 ldsm4(uint32_t a) {
    uint4 r; asm volatile("ldmatrix.sync.aligned.m8n8.x4.shared.b16 {%0,%1,%2,%3},[%4];" : "=r"(r.x), "=r"(r.y), "=r"(r.z), "=r"(r.w) : "r"(a) : "memory"); return r;
}
__device__ __forceinline__ uint4 ldsm4t(uint32_t a) {
    uint4 r; asm volatile("ldmatrix.sync.aligned.m8n8.x4.trans.shared.b16 {%0,%1,%2,%3},[%4];" : "=r"(r.x), "=r"(r.y), "=r"(r.z), "=r"(r.w) : "r"(a) : "memory"); return r;
}
__device__ __forceinline__ uint2 ldsm2(uint32_t a) {
    uint2 r; asm volatile("ldmatrix.sync.aligned.m8n8.x2.shared.b16 {%0,%1},[%2];" : "=r"(r.x), "=r"(r.y) : "r"(a) : "memory"); return r;
}
__device__ __forceinline__ void wg_fence() { asm volatile("wgmma.fence.sync.aligned;" ::: "memory"); }
__device__ __forceinline__ void wg_commit() { asm volatile("wgmma.commit_group.sync.aligned;" ::: "memory"); }
__device__ __forceinline__ void wg_wait0() { asm volatile("wgmma.wait_group.sync.aligned 0;" ::: "memory"); }
__device__ __forceinline__ uint2 ldsm2t(uint32_t a) {
    uint2 r; asm volatile("ldmatrix.sync.aligned.m8n8.x2.trans.shared.b16 {%0,%1},[%2];" : "=r"(r.x), "=r"(r.y) : "r"(a) : "memory"); return r;
}
__device__ __forceinline__ void stsm4t(uint32_t a, uint32_t x, uint32_t y, uint32_t z, uint32_t w) {
    asm volatile("stmatrix.sync.aligned.m8n8.x4.trans.shared.b16 [%0],{%1,%2,%3,%4};" ::"r"(a), "r"(x), "r"(y), "r"(z), "r"(w) : "memory");
}
__device__ __forceinline__ void stsm2(uint32_t a, uint32_t x, uint32_t y) {
    asm volatile("stmatrix.sync.aligned.m8n8.x2.shared.b16 [%0],{%1,%2};" ::"r"(a), "r"(x), "r"(y) : "memory");
}
__device__ __forceinline__ float lds32f(uint32_t a) { float v; asm volatile("ld.shared.f32 %0,[%1];" : "=f"(v) : "r"(a) : "memory"); return v; }
__device__ __forceinline__ uint4 lds128(uint32_t a) {
    uint4 v; asm volatile("ld.shared.v4.u32 {%0,%1,%2,%3},[%4];" : "=r"(v.x), "=r"(v.y), "=r"(v.z), "=r"(v.w) : "r"(a) : "memory"); return v;
}
__device__ __forceinline__ float4 lds128f(uint32_t a) {
    float4 v; asm volatile("ld.shared.v4.f32 {%0,%1,%2,%3},[%4];" : "=f"(v.x), "=f"(v.y), "=f"(v.z), "=f"(v.w) : "r"(a) : "memory"); return v;
}
__device__ __forceinline__ uint4 lds128v(uint32_t a) {
    uint4 v; asm volatile("ld.volatile.shared.v4.u32 {%0,%1,%2,%3},[%4];" : "=r"(v.x), "=r"(v.y), "=r"(v.z), "=r"(v.w) : "r"(a) : "memory"); return v;
}
__device__ __forceinline__ uint2 lds64v(uint32_t a) { uint2 v; asm volatile("ld.volatile.shared.v2.u32 {%0,%1},[%2];" : "=r"(v.x), "=r"(v.y) : "r"(a) : "memory"); return v; }
__device__ __forceinline__ uint2 lds64(uint32_t a) { uint2 v; asm volatile("ld.shared.v2.u32 {%0,%1},[%2];" : "=r"(v.x), "=r"(v.y) : "r"(a) : "memory"); return v; }
__device__ __forceinline__ float2 lds64f(uint32_t a) { float2 v; asm volatile("ld.shared.v2.f32 {%0,%1},[%2];" : "=f"(v.x), "=f"(v.y) : "r"(a) : "memory"); return v; }
__device__ __forceinline__ uint32_t lds32(uint32_t a) { uint32_t v; asm volatile("ld.shared.u32 %0,[%1];" : "=r"(v) : "r"(a) : "memory"); return v; }
__device__ __forceinline__ void sts128(uint32_t a, uint32_t x, uint32_t y, uint32_t z, uint32_t w) {
    asm volatile("st.shared.v4.u32 [%0],{%1,%2,%3,%4};" ::"r"(a), "r"(x), "r"(y), "r"(z), "r"(w) : "memory");
}
__device__ __forceinline__ void sts128(uint32_t a, const uint4& v) { sts128(a, v.x, v.y, v.z, v.w); }
__device__ __forceinline__ void sts64f(uint32_t a, float x, float y) { asm volatile("st.shared.v2.f32 [%0],{%1,%2};" ::"r"(a), "f"(x), "f"(y) : "memory"); }
__device__ __forceinline__ void sts64(uint32_t a, uint32_t x, uint32_t y) { asm volatile("st.shared.v2.u32 [%0],{%1,%2};" ::"r"(a), "r"(x), "r"(y) : "memory"); }
__device__ __forceinline__ void sts32f(uint32_t a, float x) { asm volatile("st.shared.f32 [%0],%1;" ::"r"(a), "f"(x) : "memory"); }
__device__ __forceinline__ uint32_t mapa(uint32_t a, uint32_t r) { uint32_t o; asm("mapa.shared::cluster.u32 %0,%1,%2;" : "=r"(o) : "r"(a), "r"(r)); return o; }
__device__ __forceinline__ void sta4(uint32_t dst, uint32_t bar, uint32_t x, uint32_t y, uint32_t z, uint32_t w) {
    asm volatile("st.async.weak.shared::cluster.mbarrier::complete_tx::bytes.v4.b32 [%0],{%1,%2,%3,%4},[%5];" ::"r"(dst), "r"(x), "r"(y), "r"(z), "r"(w), "r"(bar) : "memory");
}
__device__ __forceinline__ void sta4f(uint32_t dst, uint32_t bar, const float4& v) { sta4(dst, bar, __float_as_uint(v.x), __float_as_uint(v.y), __float_as_uint(v.z), __float_as_uint(v.w)); }
__device__ __forceinline__ void sta2f(uint32_t dst, uint32_t bar, float x, float y) {
    asm volatile("st.async.weak.shared::cluster.mbarrier::complete_tx::bytes.v2.f32 [%0],{%1,%2},[%3];" ::"r"(dst), "f"(x), "f"(y), "r"(bar) : "memory");
}
__device__ __forceinline__ void sta1(uint32_t dst, uint32_t bar, uint32_t x) {
    asm volatile("st.async.weak.shared::cluster.mbarrier::complete_tx::bytes.b32 [%0],%1,[%2];" ::"r"(dst), "r"(x), "r"(bar) : "memory");
}
__device__ __forceinline__ void mbar_init(uint32_t bar, int cnt) { asm volatile("mbarrier.init.shared::cta.b64 [%0],%1;" ::"r"(bar), "r"(cnt) : "memory"); }
__device__ __forceinline__ void mbar_expect(uint32_t bar, int bytes) { asm volatile("mbarrier.arrive.expect_tx.shared::cta.b64 _,[%0],%1;" ::"r"(bar), "r"(bytes) : "memory"); }
__device__ __forceinline__ void mbar_wait(uint32_t bar, uint32_t parity) {
    uint32_t ok; int it = 0;
    while (true) {
        asm volatile("{.reg .pred p; mbarrier.try_wait.parity.relaxed.cluster.shared::cta.b64 p,[%1],%2; selp.u32 %0,1,0,p;}" : "=r"(ok) : "r"(bar), "r"(parity) : "memory");
        if (ok) break;
        if (++it > (1 << 20)) __trap();
    }
    asm volatile("fence.acquire.sync_restrict::shared::cluster.cluster;" ::: "memory");
}
__device__ __forceinline__ uint32_t mbar_try(uint32_t bar) {
    uint32_t ok; asm volatile("{.reg .pred p; mbarrier.try_wait.parity.relaxed.cluster.shared::cta.b64 p,[%1],0; selp.u32 %0,1,0,p;}" : "=r"(ok) : "r"(bar) : "memory"); return ok;
}
__device__ __forceinline__ void acq_fence() { asm volatile("fence.acquire.sync_restrict::shared::cluster.cluster;" ::: "memory"); }
__device__ __forceinline__ void mbar_wait_nf(uint32_t bar) {
    uint32_t ok; int it = 0;
    while (true) {
        asm volatile("{.reg .pred p; mbarrier.try_wait.parity.shared::cta.b64 p,[%1],0; selp.u32 %0,1,0,p;}" : "=r"(ok) : "r"(bar) : "memory");
        if (ok) break;
        if (++it > (1 << 20)) __trap();
    }
}
__device__ __forceinline__ bool elect() {
    uint32_t p; asm volatile("{.reg .pred p; elect.sync _|p,0xffffffff; selp.u32 %0,1,0,p;}" : "=r"(p)); return p;
}
__device__ __forceinline__ void tma3d(uint32_t dst, const CUtensorMap* map, int x, int y, int z, uint32_t bar) {
    asm volatile("cp.async.bulk.tensor.3d.shared::cluster.global.mbarrier::complete_tx::bytes [%0],[%1,{%2,%3,%4}],[%5];" ::"r"(dst), "l"(map), "r"(x), "r"(y), "r"(z), "r"(bar) : "memory");
}
__device__ __forceinline__ void bulk_g2s(uint32_t dst, const void* src, int bytes, uint32_t bar) {
    asm volatile("cp.async.bulk.shared::cluster.global.mbarrier::complete_tx::bytes [%0],[%1],%2,[%3];" ::"r"(dst), "l"(src), "r"(bytes), "r"(bar) : "memory");
}
__device__ __forceinline__ void tma2d(uint32_t dst, const CUtensorMap* map, int x, int y, uint32_t bar) {
    asm volatile("cp.async.bulk.tensor.2d.shared::cluster.global.mbarrier::complete_tx::bytes [%0],[%1,{%2,%3}],[%4];" ::"r"(dst), "l"(map), "r"(x), "r"(y), "r"(bar) : "memory");
}
__device__ __forceinline__ void tma_red2d(const CUtensorMap* map, int x, int y, uint32_t src) {
    asm volatile("cp.reduce.async.bulk.tensor.3d.global.shared::cta.add.tile.bulk_group [%0,{%1,%2,%3}],[%4];" ::"l"(map), "r"(0), "r"(y), "r"(x), "r"(src) : "memory");
    asm volatile("cp.async.bulk.commit_group;" ::: "memory");
}
template <int ID, int N> __device__ __forceinline__ void bar_sync() { asm volatile("bar.sync %0,%1;" ::"n"(ID), "n"(N) : "memory"); }
template <int ID, int N> __device__ __forceinline__ void bar_arrive() { asm volatile("bar.arrive %0,%1;" ::"n"(ID), "n"(N) : "memory"); }
__device__ __forceinline__ uint4 ld_poll(const void* p) {
    uint4 v; asm volatile("ld.relaxed.gpu.global.v4.u32 {%0,%1,%2,%3},[%4];" : "=r"(v.x), "=r"(v.y), "=r"(v.z), "=r"(v.w) : "l"(p) : "memory"); return v;
}
__device__ __forceinline__ bool poll_bad(const uint4& a, const uint4& b, const uint4& c, const uint4& d) {
    return __any_sync(0xffffffffu, (a.w & b.w & c.w & d.w & 0x40000000u) == 0);
}
__device__ __forceinline__ void red_bf16x8(void* p, uint32_t x, uint32_t y, uint32_t z, uint32_t w) {
    asm volatile("red.relaxed.gpu.global.add.noftz.v4.bf16x2 [%0],{%1,%2,%3,%4};" ::"l"(p), "r"(x), "r"(y), "r"(z), "r"(w) : "memory");
}
__device__ __forceinline__ float ex2(float x) { float y; asm("ex2.approx.ftz.f32 %0,%1;" : "=f"(y) : "f"(x)); return y; }
__device__ __forceinline__ float rcp(float x) { float y; asm("rcp.approx.ftz.f32 %0,%1;" : "=f"(y) : "f"(x)); return y; }
__device__ __forceinline__ uint32_t clk() { uint64_t c; asm volatile("mov.u64 %0,%%clock64;" : "=l"(c)::"memory"); return (uint32_t)c; }
__device__ __forceinline__ uint32_t hadd(uint32_t a, uint32_t b) { uint32_t r; asm("add.rn.bf16x2 %0,%1,%2;" : "=r"(r) : "r"(a), "r"(b)); return r; }
__device__ __forceinline__ void cluster_sync() { asm volatile("barrier.cluster.arrive.release.aligned; barrier.cluster.wait.acquire.aligned;" ::: "memory"); }
__device__ __forceinline__ float4 sum4(float4 a, float4 b, float4 c, float4 d) {
    return make_float4((a.x + b.x) + (c.x + d.x), (a.y + b.y) + (c.y + d.y), (a.z + b.z) + (c.z + d.z), (a.w + b.w) + (c.w + d.w));
}
#define FENCE() asm volatile("griddepcontrol.launch_dependents;" ::: "memory")
template <int TB> __device__ __forceinline__ void wgmma32(float* d, const uint4& a, uint64_t desc, bool accumulate) {
    if (accumulate) asm volatile("{.reg .pred p; setp.ne.b32 p,1,0;\n"
                 "wgmma.mma_async.sync.aligned.m64n32k16.f32.bf16.bf16 {%0,%1,%2,%3,%4,%5,%6,%7,%8,%9,%10,%11,%12,%13,%14,%15},{%16,%17,%18,%19},%20,p,1,1,%21;}"
                 : "+f"(d[0]), "+f"(d[1]), "+f"(d[2]), "+f"(d[3]), "+f"(d[4]), "+f"(d[5]), "+f"(d[6]), "+f"(d[7]), "+f"(d[8]), "+f"(d[9]), "+f"(d[10]), "+f"(d[11]), "+f"(d[12]), "+f"(d[13]), "+f"(d[14]), "+f"(d[15])
                 : "r"(a.x), "r"(a.y), "r"(a.z), "r"(a.w), "l"(desc), "n"(TB));
    else asm volatile("{.reg .pred p; setp.ne.b32 p,0,0;\n"
                 "wgmma.mma_async.sync.aligned.m64n32k16.f32.bf16.bf16 {%0,%1,%2,%3,%4,%5,%6,%7,%8,%9,%10,%11,%12,%13,%14,%15},{%16,%17,%18,%19},%20,p,1,1,%21;}"
                 : "=f"(d[0]), "=f"(d[1]), "=f"(d[2]), "=f"(d[3]), "=f"(d[4]), "=f"(d[5]), "=f"(d[6]), "=f"(d[7]), "=f"(d[8]), "=f"(d[9]), "=f"(d[10]), "=f"(d[11]), "=f"(d[12]), "=f"(d[13]), "=f"(d[14]), "=f"(d[15])
                 : "r"(a.x), "r"(a.y), "r"(a.z), "r"(a.w), "l"(desc), "n"(TB));
}
template <int TB> __device__ __forceinline__ void wgmma224(float* d, const uint4& a, uint64_t desc, bool accumulate) {
    if (accumulate) asm volatile("{.reg .pred p; setp.ne.b32 p,1,0;\n"
                 "wgmma.mma_async.sync.aligned.m64n224k16.f32.bf16.bf16 {%0,%1,%2,%3,%4,%5,%6,%7,%8,%9,%10,%11,%12,%13,%14,%15,%16,%17,%18,%19,%20,%21,%22,%23,%24,%25,%26,%27,%28,%29,%30,%31,%32,%33,%34,%35,%36,%37,%38,%39,%40,%41,%42,%43,%44,%45,%46,%47,%48,%49,%50,%51,%52,%53,%54,%55,%56,%57,%58,%59,%60,%61,%62,%63,%64,%65,%66,%67,%68,%69,%70,%71,%72,%73,%74,%75,%76,%77,%78,%79,%80,%81,%82,%83,%84,%85,%86,%87,%88,%89,%90,%91,%92,%93,%94,%95,%96,%97,%98,%99,%100,%101,%102,%103,%104,%105,%106,%107,%108,%109,%110,%111},{%112,%113,%114,%115},%116,p,1,1,%117;}"
                 : "+f"(d[0]), "+f"(d[1]), "+f"(d[2]), "+f"(d[3]), "+f"(d[4]), "+f"(d[5]), "+f"(d[6]), "+f"(d[7]), "+f"(d[8]), "+f"(d[9]), "+f"(d[10]), "+f"(d[11]), "+f"(d[12]), "+f"(d[13]), "+f"(d[14]), "+f"(d[15]), "+f"(d[16]), "+f"(d[17]), "+f"(d[18]), "+f"(d[19]), "+f"(d[20]), "+f"(d[21]), "+f"(d[22]), "+f"(d[23]), "+f"(d[24]), "+f"(d[25]), "+f"(d[26]), "+f"(d[27]), "+f"(d[28]), "+f"(d[29]), "+f"(d[30]), "+f"(d[31]), "+f"(d[32]), "+f"(d[33]), "+f"(d[34]), "+f"(d[35]), "+f"(d[36]), "+f"(d[37]), "+f"(d[38]), "+f"(d[39]), "+f"(d[40]), "+f"(d[41]), "+f"(d[42]), "+f"(d[43]), "+f"(d[44]), "+f"(d[45]), "+f"(d[46]), "+f"(d[47]), "+f"(d[48]), "+f"(d[49]), "+f"(d[50]), "+f"(d[51]), "+f"(d[52]), "+f"(d[53]), "+f"(d[54]), "+f"(d[55]), "+f"(d[56]), "+f"(d[57]), "+f"(d[58]), "+f"(d[59]), "+f"(d[60]), "+f"(d[61]), "+f"(d[62]), "+f"(d[63]), "+f"(d[64]), "+f"(d[65]), "+f"(d[66]), "+f"(d[67]), "+f"(d[68]), "+f"(d[69]), "+f"(d[70]), "+f"(d[71]), "+f"(d[72]), "+f"(d[73]), "+f"(d[74]), "+f"(d[75]), "+f"(d[76]), "+f"(d[77]), "+f"(d[78]), "+f"(d[79]), "+f"(d[80]), "+f"(d[81]), "+f"(d[82]), "+f"(d[83]), "+f"(d[84]), "+f"(d[85]), "+f"(d[86]), "+f"(d[87]), "+f"(d[88]), "+f"(d[89]), "+f"(d[90]), "+f"(d[91]), "+f"(d[92]), "+f"(d[93]), "+f"(d[94]), "+f"(d[95]), "+f"(d[96]), "+f"(d[97]), "+f"(d[98]), "+f"(d[99]), "+f"(d[100]), "+f"(d[101]), "+f"(d[102]), "+f"(d[103]), "+f"(d[104]), "+f"(d[105]), "+f"(d[106]), "+f"(d[107]), "+f"(d[108]), "+f"(d[109]), "+f"(d[110]), "+f"(d[111])
                 : "r"(a.x), "r"(a.y), "r"(a.z), "r"(a.w), "l"(desc), "n"(TB));
    else asm volatile("{.reg .pred p; setp.ne.b32 p,0,0;\n"
                 "wgmma.mma_async.sync.aligned.m64n224k16.f32.bf16.bf16 {%0,%1,%2,%3,%4,%5,%6,%7,%8,%9,%10,%11,%12,%13,%14,%15,%16,%17,%18,%19,%20,%21,%22,%23,%24,%25,%26,%27,%28,%29,%30,%31,%32,%33,%34,%35,%36,%37,%38,%39,%40,%41,%42,%43,%44,%45,%46,%47,%48,%49,%50,%51,%52,%53,%54,%55,%56,%57,%58,%59,%60,%61,%62,%63,%64,%65,%66,%67,%68,%69,%70,%71,%72,%73,%74,%75,%76,%77,%78,%79,%80,%81,%82,%83,%84,%85,%86,%87,%88,%89,%90,%91,%92,%93,%94,%95,%96,%97,%98,%99,%100,%101,%102,%103,%104,%105,%106,%107,%108,%109,%110,%111},{%112,%113,%114,%115},%116,p,1,1,%117;}"
                 : "=f"(d[0]), "=f"(d[1]), "=f"(d[2]), "=f"(d[3]), "=f"(d[4]), "=f"(d[5]), "=f"(d[6]), "=f"(d[7]), "=f"(d[8]), "=f"(d[9]), "=f"(d[10]), "=f"(d[11]), "=f"(d[12]), "=f"(d[13]), "=f"(d[14]), "=f"(d[15]), "=f"(d[16]), "=f"(d[17]), "=f"(d[18]), "=f"(d[19]), "=f"(d[20]), "=f"(d[21]), "=f"(d[22]), "=f"(d[23]), "=f"(d[24]), "=f"(d[25]), "=f"(d[26]), "=f"(d[27]), "=f"(d[28]), "=f"(d[29]), "=f"(d[30]), "=f"(d[31]), "=f"(d[32]), "=f"(d[33]), "=f"(d[34]), "=f"(d[35]), "=f"(d[36]), "=f"(d[37]), "=f"(d[38]), "=f"(d[39]), "=f"(d[40]), "=f"(d[41]), "=f"(d[42]), "=f"(d[43]), "=f"(d[44]), "=f"(d[45]), "=f"(d[46]), "=f"(d[47]), "=f"(d[48]), "=f"(d[49]), "=f"(d[50]), "=f"(d[51]), "=f"(d[52]), "=f"(d[53]), "=f"(d[54]), "=f"(d[55]), "=f"(d[56]), "=f"(d[57]), "=f"(d[58]), "=f"(d[59]), "=f"(d[60]), "=f"(d[61]), "=f"(d[62]), "=f"(d[63]), "=f"(d[64]), "=f"(d[65]), "=f"(d[66]), "=f"(d[67]), "=f"(d[68]), "=f"(d[69]), "=f"(d[70]), "=f"(d[71]), "=f"(d[72]), "=f"(d[73]), "=f"(d[74]), "=f"(d[75]), "=f"(d[76]), "=f"(d[77]), "=f"(d[78]), "=f"(d[79]), "=f"(d[80]), "=f"(d[81]), "=f"(d[82]), "=f"(d[83]), "=f"(d[84]), "=f"(d[85]), "=f"(d[86]), "=f"(d[87]), "=f"(d[88]), "=f"(d[89]), "=f"(d[90]), "=f"(d[91]), "=f"(d[92]), "=f"(d[93]), "=f"(d[94]), "=f"(d[95]), "=f"(d[96]), "=f"(d[97]), "=f"(d[98]), "=f"(d[99]), "=f"(d[100]), "=f"(d[101]), "=f"(d[102]), "=f"(d[103]), "=f"(d[104]), "=f"(d[105]), "=f"(d[106]), "=f"(d[107]), "=f"(d[108]), "=f"(d[109]), "=f"(d[110]), "=f"(d[111])
                 : "r"(a.x), "r"(a.y), "r"(a.z), "r"(a.w), "l"(desc), "n"(TB));
}
template <int TB> __device__ __forceinline__ void wgmma112(float* d, uint64_t da, uint64_t db, bool accumulate) {
    if (accumulate) asm volatile("{.reg .pred p; setp.ne.b32 p,1,0;\n"
                 "wgmma.mma_async.sync.aligned.m64n112k16.f32.bf16.bf16 {%0,%1,%2,%3,%4,%5,%6,%7,%8,%9,%10,%11,%12,%13,%14,%15,%16,%17,%18,%19,%20,%21,%22,%23,%24,%25,%26,%27,%28,%29,%30,%31,%32,%33,%34,%35,%36,%37,%38,%39,%40,%41,%42,%43,%44,%45,%46,%47,%48,%49,%50,%51,%52,%53,%54,%55},%56,%57,p,1,1,0,%58;}"
                 : "+f"(d[0]), "+f"(d[1]), "+f"(d[2]), "+f"(d[3]), "+f"(d[4]), "+f"(d[5]), "+f"(d[6]), "+f"(d[7]), "+f"(d[8]), "+f"(d[9]), "+f"(d[10]), "+f"(d[11]), "+f"(d[12]), "+f"(d[13]), "+f"(d[14]), "+f"(d[15]), "+f"(d[16]), "+f"(d[17]), "+f"(d[18]), "+f"(d[19]), "+f"(d[20]), "+f"(d[21]), "+f"(d[22]), "+f"(d[23]), "+f"(d[24]), "+f"(d[25]), "+f"(d[26]), "+f"(d[27]), "+f"(d[28]), "+f"(d[29]), "+f"(d[30]), "+f"(d[31]), "+f"(d[32]), "+f"(d[33]), "+f"(d[34]), "+f"(d[35]), "+f"(d[36]), "+f"(d[37]), "+f"(d[38]), "+f"(d[39]), "+f"(d[40]), "+f"(d[41]), "+f"(d[42]), "+f"(d[43]), "+f"(d[44]), "+f"(d[45]), "+f"(d[46]), "+f"(d[47]), "+f"(d[48]), "+f"(d[49]), "+f"(d[50]), "+f"(d[51]), "+f"(d[52]), "+f"(d[53]), "+f"(d[54]), "+f"(d[55])
                 : "l"(da), "l"(db), "n"(TB));
    else asm volatile("{.reg .pred p; setp.ne.b32 p,0,0;\n"
                 "wgmma.mma_async.sync.aligned.m64n112k16.f32.bf16.bf16 {%0,%1,%2,%3,%4,%5,%6,%7,%8,%9,%10,%11,%12,%13,%14,%15,%16,%17,%18,%19,%20,%21,%22,%23,%24,%25,%26,%27,%28,%29,%30,%31,%32,%33,%34,%35,%36,%37,%38,%39,%40,%41,%42,%43,%44,%45,%46,%47,%48,%49,%50,%51,%52,%53,%54,%55},%56,%57,p,1,1,0,%58;}"
                 : "=f"(d[0]), "=f"(d[1]), "=f"(d[2]), "=f"(d[3]), "=f"(d[4]), "=f"(d[5]), "=f"(d[6]), "=f"(d[7]), "=f"(d[8]), "=f"(d[9]), "=f"(d[10]), "=f"(d[11]), "=f"(d[12]), "=f"(d[13]), "=f"(d[14]), "=f"(d[15]), "=f"(d[16]), "=f"(d[17]), "=f"(d[18]), "=f"(d[19]), "=f"(d[20]), "=f"(d[21]), "=f"(d[22]), "=f"(d[23]), "=f"(d[24]), "=f"(d[25]), "=f"(d[26]), "=f"(d[27]), "=f"(d[28]), "=f"(d[29]), "=f"(d[30]), "=f"(d[31]), "=f"(d[32]), "=f"(d[33]), "=f"(d[34]), "=f"(d[35]), "=f"(d[36]), "=f"(d[37]), "=f"(d[38]), "=f"(d[39]), "=f"(d[40]), "=f"(d[41]), "=f"(d[42]), "=f"(d[43]), "=f"(d[44]), "=f"(d[45]), "=f"(d[46]), "=f"(d[47]), "=f"(d[48]), "=f"(d[49]), "=f"(d[50]), "=f"(d[51]), "=f"(d[52]), "=f"(d[53]), "=f"(d[54]), "=f"(d[55])
                 : "l"(da), "l"(db), "n"(TB));
}
__device__ __forceinline__ uint64_t mdesc(uint32_t addr, uint32_t lbo, uint32_t sbo, int swz) {
    return (uint64_t)((addr & 0x3FFFF) >> 4) | ((uint64_t)(lbo >> 4) << 16) | ((uint64_t)(sbo >> 4) << 32) | ((uint64_t)swz << 62);
}
template <int N> __device__ __forceinline__ void wg_wait() { asm volatile("wgmma.wait_group.sync.aligned %0;" ::"n"(N) : "memory"); }
__device__ __forceinline__ void bar_sync(int id, int n) { asm volatile("bar.sync %0,%1;" ::"r"(id), "r"(n) : "memory"); }
__device__ __forceinline__ void bar_arrive(int id, int n) { asm volatile("bar.arrive %0,%1;" ::"r"(id), "r"(n) : "memory"); }
__device__ __forceinline__ int ld_flag(const int* p) { int v; asm volatile("ld.relaxed.gpu.global.s32 %0,[%1];" : "=r"(v) : "l"(p) : "memory"); return v; }
__device__ __forceinline__ void st_flag(int* p, int v) { asm volatile("st.relaxed.gpu.global.s32 [%0],%1;" ::"l"(p), "r"(v) : "memory"); }
__device__ __forceinline__ void fence_gpu() { asm volatile("fence.acq_rel.gpu;" ::: "memory"); }
__device__ __forceinline__ void wait_flag(const int* p, int need) {
    int it = 0;
    while (ld_flag(p) < need) { if (++it > (1 << 20)) __trap(); }
    fence_gpu();
}
__device__ __forceinline__ void retire(int total) {
    fence_gpu();
    if (atomicAdd(&g_FLAG[F_DONE * 32], 1) == total - 1) { fence_gpu(); for (int i = 0; i < 132; i++) st_flag(&g_FLAG[i * 32], 0); }
}
__device__ __forceinline__ void sts32(uint32_t a, uint32_t x) { asm volatile("st.shared.u32 [%0],%1;" ::"r"(a), "r"(x) : "memory"); }
__device__ __forceinline__ uint32_t packv(float lo, float hi) { uint32_t r; asm volatile("cvt.rn.bf16x2.f32 %0,%1,%2;" : "=r"(r) : "f"(hi), "f"(lo)); return r; }
constexpr float LOG2E = 1.4426950408889634f;

#define POLL_DELAY 500
#define DBGW 1
#define TMA_DELAY 150
constexpr int NST = 5;
constexpr int S_KQ = 0, S_V = 7168, S_XX = 14336, STGB = RECC, XB = 7168;
constexpr int R_BK = 31744;
constexpr int R_STG = R_BK + 3 * 8192;
constexpr int R_ST2 = R_STG + NST * STGB;
constexpr int R_OUT = R_ST2 + 2 * XB;
constexpr int R_W0 = 0;
constexpr int R_MB = R_OUT + 2 * 7168;
constexpr int R_SXJ = R_MB + 4 * 3584;
constexpr int R_SMI = R_SXJ + 1024;
constexpr int R_SMX = R_SMI + 2048;
constexpr int R_SMM = R_SMX + 1024;
constexpr int R_SME = R_SMM + 1024;
constexpr int R_UP = R_SME + 512;
constexpr int R_UB = R_UP + 8192;
constexpr int R_SXI = R_UB + 8192;
constexpr int R_LX = R_SXI + 4096;
constexpr int R_PB = R_LX + 2 * 1024;
constexpr int R_BAR = R_PB + 4 * 2176;
constexpr int B_KV = 0, B_SX = 512, B_SM = 1024, B_L1 = 1536, B_L2 = 2048, B_BK = 2560, B_F = 3072;
constexpr int R_Z = R_BAR + 3584;
constexpr int R_SMEM = R_Z + 7168;
constexpr int F_B = 0, F_A = 114688;
static_assert(F_A + 6 * 16384 <= R_BAR, "folding buffers");
static_assert(R_SMEM <= 232448, "smem");
constexpr uint32_t ONE2 = 0x3f803f80u, CNT16 = 0x40000000u, CNT1 = 0x3e003e00u;
enum { BR = 1, BX, BG, BS, BU, BL, BO, BV, BH };

#define DBG(i)

struct Maps { CUtensorMap x, out, acc, q112, o112, k8, v8, q224, o224, rk, rv, u8, o8; };

__device__ __forceinline__ void load_stage(uint32_t sb, int seg, uint32_t stg, int h, int c, const CUtensorMap* mapX) {
    const uint32_t bar = sb + R_BAR + B_KV + seg * 8, dst = sb + R_STG + stg;
    const int r = ((seg % RING) * 16 + h) * 4;
    bulk_g2s(dst, g_REC + (size_t)(r + c) * RECC, RECC, bar);
    tma3d(sb + R_ST2 + (seg & 1) * XB, mapX, 0, 32 * seg, 7 * c, bar);
}

__host__ __device__ constexpr int KS(int j) { return (j & 1) ? j >> 1 : 3 + (j >> 1); }

__global__ void __cluster_dims__(4, 1, 1) __launch_bounds__(256, 1)
k_rec(const __nv_bfloat16* __restrict__ mem0, const __nv_bfloat16* __restrict__ x, const __grid_constant__ Maps maps, int total) {
    extern __shared__ __align__(1024) uint8_t smem[];
    const uint32_t sb = smem_u32(smem);
    const int tid = threadIdx.x, wid = __shfl_sync(0xffffffffu, tid >> 5, 0), w = wid & 3;
    const int lane = __shfl_sync(0xffffffffu, tid & 31, tid & 31);
    const int g = lane >> 2, t = lane & 3;
    const int h = blockIdx.x >> 2, c = blockIdx.x & 3;

    FENCE();
    if (tid == 0) GT(0, 0);
    if (sb != 1024 + (sb & 0xff000000u)) __trap();
    if (tid < 7) asm volatile("prefetch.tensormap [%0];" ::"l"(&maps.x + tid) : "memory");
    if (elect()) {
#pragma unroll 1
        for (int i = wid * 8; i < wid * 8 + 8; i++) mbar_init(sb + R_BAR + B_F + i * 8, (i & 31) < 18 ? 1 : 4);
        asm volatile("fence.mbarrier_init.release.cluster;" ::: "memory");
    }
    __syncwarp();
    if (lane < 8 && w * 8 + lane < 18) mbar_expect(sb + R_BAR + B_F + (wid * 8 + lane) * 8, w * 8 + lane < 4 ? 14336 : 16384);
    sts128(sb + R_Z + tid * 16, 0u, 0u, 0u, 0u); sts128(sb + R_Z + 3072 + tid * 16, 0u, 0u, 0u, 0u);
    asm volatile("fence.proxy.async.shared::cta;" ::: "memory");
    asm volatile("barrier.cluster.arrive.relaxed.aligned; barrier.cluster.wait.aligned;" ::: "memory");
    if (tid == 0) GT(0, 5);
    auto opq = [&](uint32_t x) { return __shfl_sync(0xffffffffu, x, lane); };
    const uint32_t lw = opq(sb + lane * 16 + w * 3584);
    uint4 wr[7][6];
    {
        const int M = wid >> 2;
        const uint32_t fb = sb + R_BAR + B_F + M * 256;
        const uint32_t bs = sb + F_B + M * 57344, as = sb + F_A + M * 49152;
        auto load_a = [&](int it) {
            const int p = (it >> 1) == 6 ? 0 : (it >> 1) + 1;
            asm volatile("cp.async.bulk.tensor.4d.shared::cluster.global.mbarrier::complete_tx::bytes.multicast::cluster [%0],[%1,{%2,%3,%4,%5}],[%6],%7;"
                         ::"r"(as + (it % 3) * 16384 + c * 4096), "l"(M ? &maps.v8 : &maps.k8), "r"(0), "r"(0), "r"(4 * h + 2 * (it & 1)), "r"(14 * c + 2 * KS(p)),
                           "r"(fb + (4 + it) * 8), "h"((uint16_t)15) : "memory");
        };
        if (w == c) {
            if (elect()) {
#pragma unroll 1
                for (int e = 0; e < 4; e++) {
                    if (M == 0) tma2d(bs + e * 14336, &maps.q112, h * 256 + 64 * e, 112 * c, fb + e * 8);
                    else tma3d(bs + e * 14336, &maps.o112, 0, h * 256 + 64 * e, 7 * c, fb + e * 8);
                    if (e < 3) load_a(e);
                }
            }
            __syncwarp();
        }
        {
            const int n = blockIdx.x;
            const uint4* p = (const uint4*)(x + (size_t)(32 * n + 16 * (wid & 1) + g) * D) + t;
            uint4 l[4], q[4];
#pragma unroll
            for (int i = 0; i < 4; i++) { const int j = min((wid >> 1) + 4 * i, 13); l[i] = __ldg(p + 4 * j); q[i] = __ldg(p + 8 * 56 + 4 * j); }
            if (w != c) {
                const int kind = M * 3 + ((w - c - 1) & 3);
                if (elect()) {
#pragma unroll 1
                    for (int i = 0; i < 64; i++) mbar_init(sb + R_BAR + kind * 512 + i * 8, 1);
                    asm volatile("fence.mbarrier_init.release.cluster;" ::: "memory");
                }
                __syncwarp();
                const int bytes = kind == 0 ? STGB + XB : (kind == 1 ? 512 : (kind == 2 ? 768 + 1024 : (kind == 3 ? 1024 : (kind == 4 ? 2176 : 8192))));
                mbar_expect(sb + R_BAR + kind * 512 + lane * 8, bytes); mbar_expect(sb + R_BAR + kind * 512 + 256 + lane * 8, bytes);
            }
            if (tid == 0) GT(0, 6);
            if (elect()) {
                if (wid < 4) asm volatile("cp.async.bulk.tensor.3d.global.shared::cta.tile.bulk_group [%0,{%1,%2,%3}],[%4];" ::"l"(&maps.out), "r"(0), "r"(32 * n), "r"(8 + 2 * w), "r"(sb + R_Z) : "memory");
                else asm volatile("cp.async.bulk.global.shared::cta.bulk_group [%0],[%1],2112;" ::"l"(g_ACC + (n * 4 + w) * 2112), "r"(sb + R_Z) : "memory");
                asm volatile("cp.async.bulk.commit_group;" ::: "memory");
            }
            __syncwarp();
            if (tid == 0) GT(0, 7);
#pragma unroll
            for (int i = 0; i < 4; i++) {
                uint4* o = g_XA + (2 * n + (wid & 1)) * 896 + 64 * min((wid >> 1) + 4 * i, 13) + lane;
                o[0] = make_uint4(l[i].x, q[i].x, l[i].y, q[i].y); o[32] = make_uint4(l[i].z, q[i].z, l[i].w, q[i].w);
            }
        }
        GF(0, 0);
        const uint32_t rempty = mapa(fb + 18 * 8, w);
        const uint64_t db = M == 0 ? mdesc(bs, 16, 1024, 1) : mdesc(bs, 2048, 256, 3);
        const float sc = M ? 1.f : LOG2E / 16.f;
        auto release = [&](int it) {
            if (it + 3 < 14) {
                if (elect()) asm volatile("mbarrier.arrive.relaxed.cluster.shared::cluster.b64 _,[%0];" ::"r"(rempty + it * 8) : "memory");
                __syncwarp();
                if (w == c) { mbar_wait(fb + (18 + it) * 8, 0); if (elect()) load_a(it + 3); __syncwarp(); }
            }
        };
#pragma unroll
        for (int m = 0; m < 7; m++)
#pragma unroll
            for (int j = 0; j < 6; j++) wr[m][j] = make_uint4(0, 0, 0, 0);
#pragma unroll 1
        for (int it = 0; it < 14; it += 2) {
            float d[56];
#pragma unroll
            for (int hf = 0; hf < 2; hf++) {
                mbar_wait_nf(fb + 2 * hf * 8); mbar_wait_nf(fb + (2 * hf + 1) * 8);
                mbar_wait_nf(fb + (4 + it + hf) * 8);
                GF(0, it + hf + 1);
                const uint64_t da = mdesc(as + ((it + hf) % 3) * 16384, 16, 2048, 1);
                if (M == 0) {
                    wg_fence();
#pragma unroll
                    for (int k = 0; k < 8; k++) wgmma112<0>(d, da + (((k >> 2) * 1024 + (k & 3) * 32) >> 4), db + (((2 * hf + (k >> 2)) * 14336 + (k & 3) * 32) >> 4), hf | k);
                    wg_commit();
                } else {
                    wg_fence();
#pragma unroll
                    for (int k = 0; k < 8; k++) wgmma112<1>(d, da + (((k >> 2) * 1024 + (k & 3) * 32) >> 4), db + (((2 * hf + (k >> 2)) * 14336 + (k & 3) * 512) >> 4), hf | k);
                    wg_commit();
                }
            }
            wg_wait<1>(); release(it);
            wg_wait<0>(); release(it + 1);
            if (it == 2 && elect()) {
                asm volatile("cp.async.bulk.wait_group 0; fence.proxy.async.global;" ::: "memory");
                asm volatile("red.release.gpu.global.add.s32 [%0],1;" ::"l"(&g_FLAG[F_ZERO * 32]) : "memory");
            }
            __syncwarp();
            uint32_t q[28];
#pragma unroll
            for (int i = 0; i < 28; i++) q[i] = packv(d[2 * i] * sc, d[2 * i + 1] * sc);
#define PUT(j) _Pragma("unroll") for (int m = 0; m < 7; m++) wr[m][j] = make_uint4(movm(q[4 * m]), movm(q[4 * m + 2]), movm(q[4 * m + 1]), movm(q[4 * m + 3]))
            switch (it) {
            case 0: PUT(0); break;
            case 2: PUT(1); break;
            case 4: PUT(2); break;
            case 6: PUT(3); break;
            case 8: PUT(4); break;
            case 10: PUT(5); break;
            default:
                bar_sync<BX, 256>();
#pragma unroll
                for (int m = 0; m < 7; m++) sts128(lw + R_W0 + M * 14336 + m * 512, movm(q[4 * m]), movm(q[4 * m + 2]), movm(q[4 * m + 1]), movm(q[4 * m + 3]));
            }
        }
    }
    if (tid == 0) { wait_flag(&g_FLAG[F_ZERO * 32], 512); GT(0, 1); }
    cluster_sync();
    const uint32_t l16 = opq(sb + lane * 16), l8 = opq(sb + lane * 8);
    const uint32_t lp = opq(sb + (lane & 7) * 16 + ((lane >> 4) + ((lane >> 2) & 2)) * 128);
    const uint32_t rsb = mapa(sb, (c + w) & 3);
    const int tl0 = 6 + 2 * w, tl2 = w == 3 ? 3 : 2 * w, tl3 = w < 2 ? 1 : 5;

    if (wid < 4) {
        const int poff = (w * 4 + (lane >> 3)) * 256 + (lane & 7) * 16;
        const uint8_t* pp = g_ACC + poff;
        uint4 v0, v1, v2, v3;
        {
            const uint32_t* p = (const uint32_t*)(mem0 + g * D + 112 * w + 2 * t);
            const uint32_t a = p[4], b = p[20];
            v0 = make_uint4(p[24], p[28], p[0], (a & 0xffffu) | CNT16); v1 = make_uint4(p[32], p[36], p[8], (a >> 16) | CNT16);
            v2 = make_uint4(p[40], p[44], p[16], (b & 0xffffu) | CNT16); v3 = make_uint4(p[48], p[52], p[12], (b >> 16) | CNT16);
        }
        const int rdelta = ((0x2130 >> (4 * w)) & 3) * 4096 + (c - w) * 1024;
        const uint32_t rdst = opq(rsb + R_SMM + ((4 - w) & 3) * 256 + lane * 8);
        uint32_t rbar = opq(rsb + R_BAR + B_SM + (lw & 15));
        const uint32_t psel = (w & 1) ? 0x7632u : 0x7610u;
        const uint32_t mb = lw + R_MB, ac = opq(l16 + R_MB + c * 3584), a8w = opq(l8 + w * 256);
        uint32_t vaA = opq(sb + R_STG + S_V + (lane & 15) * 16 + (tl0 + (lane >> 4)) * 512), vaB = opq(sb + R_STG + S_V + (lane & 15) * 16 + (lane < 16 ? tl2 : tl3) * 512);
        uint32_t kq = opq(lp + R_STG + S_KQ + w * 1792);
        const uint32_t smt = opq(sb + R_SMI + w * 256 + t * 64 + g * 4);
        uint32_t roff = opq(poff + rdelta + 128);
        const uint32_t rdump = 32 * 16384 + 128;
        const uint32_t uba = opq(sb + R_UB + (lane < 16 ? tl0 + (lane >> 3) : (lane < 24 ? tl2 : tl3)) * 128 + (lane & 7) * 16);
        uint32_t stg = 0;
        mbar_wait_nf(sb + R_BAR + B_KV);
        acq_fence();
        if (tid == 0) GT(0, 2);
#pragma unroll 1
        for (int s = 0; s < NSEG; s++) {
            const uint32_t bar = sb + R_BAR + s * 8;
            const uint4 k0 = ldsm4(kq), k1 = ldsm4(kq + 512), k2 = ldsm4(kq + 1024), k3 = ldsm4(kq + 1536);
            uint4 w0[7];
#pragma unroll
            for (int m = 0; m < 7; m++) if (m != 3 && m != 5) w0[m] = lds128v(lw + R_W0 + m * 512);
            DBG(12);
            FENCE();
            if (__builtin_expect(poll_bad(v0, v1, v2, v3), 0)) {
                int it = 0;
                uint32_t a = lw + (R_BK - w * 3072), an = a + 8192;
                do {
                    asm volatile("cp.async.commit_group;" ::: "memory");
                    asm volatile("cp.async.cg.shared.global [%0],[%1],16; cp.async.cg.shared.global [%0+6144],[%1+12288],16;"
                                 "cp.async.cg.shared.global [%0+2048],[%1+4096],16; cp.async.cg.shared.global [%0+4096],[%1+8192],16;" ::"r"(an), "l"(pp) : "memory");
                    if (it == 0) mbar_wait_nf(bar + B_BK); else asm volatile("cp.async.wait_group 0;" ::: "memory");
                    v0 = lds128(a); v1 = lds128(a + 6144); v2 = lds128(a + 2048); v3 = lds128(a + 4096);
                    a = an; an ^= 24576;
                    if (++it > (1 << 20)) __trap();
                } while (poll_bad(v0, v1, v2, v3));
            }
            const uint32_t b[14] = {v0.z | (lw & 15), __byte_perm(v0.w, v1.w, 0x5410), v1.z | (lw & 15), v3.z | (lw & 15), v2.z | (lw & 15), __byte_perm(v2.w, v3.w, 0x5410),
                                    v0.x, v0.y, v1.x, v1.y, v2.x, v2.y, v3.x, v3.y};
            float acc[7][4], sx[4], sy[4];
#define A(m, j) do { if ((j) == 0) mmaz(acc[m], w0[m], b[6], b[7]); else mma(acc[m], wr[m][(j) ? (j) - 1 : 0], b[2 * KS(j)], b[2 * KS(j) + 1]); } while (0)
#define ST(j) stsm2(mb + (j) * 256, b[2 * (j)], b[2 * (j) + 1])
#define TR(m) do { tb[2 * (m)] = movm(pack(acc[m][0], acc[m][1])); tb[2 * (m) + 1] = movm(pack(acc[m][2], acc[m][3])); } while (0)
            uint32_t tb[14];
            DBG(13);
            mmaz(sx, k3, b[12], b[13]); A(0, 0); FENCE();
            mmaz(sy, k2, b[10], b[11]); ST(6); A(1, 0); ST(5); FENCE();
            mma(sx, k2, b[8], b[9]); A(0, 1); ST(4); FENCE();
            mma(sy, k1, b[6], b[7]); A(1, 1); ST(3); FENCE();
            mma(sx, k1, b[4], b[5]); A(0, 2); ST(0); FENCE();
            mma(sy, k0, b[2], b[3]); A(1, 2); ST(2); FENCE();
            mma(sx, k0, b[0], b[1]); A(0, 3); ST(1); FENCE();
            A(6, 0); w0[3] = lds128(lw + R_W0 + 3 * 512); A(1, 3); FENCE();
            A(4, 0); w0[5] = lds128(lw + R_W0 + 5 * 512); A(0, 4); FENCE();
            A(6, 1); sts64f(a8w + R_SXJ, sx[0] + sy[2], sx[1] + sy[3]); A(1, 4);
            bar_sync<BX, 256>();
            acq_fence();
            A(4, 1); A(0, 5); A(6, 2); A(1, 5); FENCE();
            DBG(1);
            A(4, 2); A(0, 6); FENCE(); A(6, 3); A(1, 6); FENCE();
            A(2, 0); A(3, 0); FENCE(); A(6, 4); A(5, 0); FENCE();
            A(2, 1); TR(0); A(3, 1); FENCE(); A(6, 5); A(5, 1); FENCE();
            A(2, 2); TR(1); A(3, 2); FENCE(); A(6, 6); A(5, 2); const uint4 am0 = ldsm4(ac); FENCE();
            A(2, 3); A(3, 3); const uint2 am3 = ldsm2(ac + 1536); FENCE(); A(4, 3); A(5, 3); const uint4 am1 = ldsm4(ac + 512); FENCE();
            const uint32_t j0 = pack(acc[6][0], acc[6][1]), j1 = pack(acc[6][2], acc[6][3]);
            A(2, 4); tb[12] = movm(j0); A(3, 4); tb[13] = movm(j1); FENCE(); A(4, 4); A(5, 4); const uint4 am2 = ldsm4(ac + 1024); FENCE();
            A(2, 5); A(3, 5); FENCE(); A(4, 5); A(5, 5); FENCE();
            A(2, 6); A(3, 6); FENCE(); A(4, 6); A(5, 6); bar_arrive<BH, 256>(); FENCE();
            DBG(2);
            float sa[4], sc[4], se[4], sf[4];
            const uint4 tq0 = make_uint4(tb[0], tb[2], tb[1], tb[3]), tq3 = make_uint4(tb[12], j0, tb[13], j1);
            mmaz(sa, tq0, am0.x, am0.y); TR(2); FENCE(); mmaz(sc, tq0, am0.z, am0.w); TR(3); FENCE(); mmaz(se, tq3, am3.x, am3.y); TR(4); FENCE();
            TR(5); FENCE();
            const uint4 tq1 = make_uint4(tb[4], tb[6], tb[5], tb[7]), tq2 = make_uint4(tb[8], tb[10], tb[9], tb[11]);
            mma(sa, tq1, am1.x, am1.y); mma(sc, tq1, am1.z, am1.w); FENCE(); mma(se, tq2, am2.x, am2.y); mmaz(sf, tq2, am2.z, am2.w);
            bar_arrive<BG, 256>();
            FENCE();
            sts32f(smt, ((sa[0] + sc[2]) + se[0]) + sf[2]); sts32f(smt + 32, ((sa[1] + sc[3]) + se[1]) + sf[3]);
            DBG(3);
            bar_sync<BS, 128>();
            float s0, s1;
            {
                const float2 p0 = lds64f(l8 + R_SMI), p1 = lds64f(l8 + R_SMI + 256), p2 = lds64f(l8 + R_SMI + 512), p3 = lds64f(l8 + R_SMI + 768);
                s0 = ((p0.x + p1.x) + p2.x) + p3.x; s1 = ((p0.y + p1.y) + p2.y) + p3.y;
                if (w) sta2f(rdst, rbar, s0, s1);
            }
            DBG(4);
            const uint32_t one2a = ONE2 | (lw & 15), one2b = ONE2 | (lp & 15);
            float o[5][4];
            uint4 ub;
            uint2 h0, h1, h2, h3;
            uint32_t smok;
            {
                const uint32_t sxok = mbar_try(bar + B_SX);
                const uint4 va0 = ldsm4t(vaA), vc0 = ldsm4t(vaB), va1 = ldsm4t(vaA + 256), vc1 = ldsm4t(vaB + 256);
                FENCE();
                if (!sxok) mbar_wait(bar + B_SX, 0);
                const uint4 ea = ldsm4t(lp + R_SME), eb = ldsm4t(lp + R_SME + 256);
                bar_sync<BV, 256>();
                const uint2 e0 = lds64(a8w + R_UP), e1 = lds64(a8w + R_UP + 1024), e2 = lds64(a8w + R_UP + 2048), e3 = lds64(a8w + R_UP + 3072);
                FENCE();
                mmaz(o[4], ea, one2a, one2b); mmaz(o[0], ea, va0.x, va0.y); mmaz(o[1], ea, va0.z, va0.w); mmaz(o[2], ea, vc0.x, vc0.y); mmaz(o[3], ea, vc0.z, vc0.w);
                smok = mbar_try(bar + B_SM);
                FENCE();
                mma(o[4], eb, one2a, one2b); mma(o[0], eb, va1.x, va1.y); mma(o[1], eb, va1.z, va1.w); mma(o[2], eb, vc1.x, vc1.y); mma(o[3], eb, vc1.z, vc1.w);
                h0 = e0; h1 = e1; h2 = e2; h3 = e3;
            }
            DBG(5);
            FENCE();
            if (!smok) mbar_wait(bar + B_SM, 0);
            acq_fence();
            DBG(7);
            const float2 p1 = lds64f(l8 + R_SMM + 256), p2 = lds64f(l8 + R_SMM + 512), p3 = lds64f(l8 + R_SMM + 768);
            bar_sync<BU, 256>();
            const uint2 u0 = lds64(a8w + R_UP + 4096), u1 = lds64(a8w + R_UP + 5120), u2 = lds64(a8w + R_UP + 6144), u3 = lds64(a8w + R_UP + 7168);
            ub.z = hadd(hadd(h0.x, h1.x), hadd(h2.x, h3.x)); ub.w = hadd(hadd(h0.y, h1.y), hadd(h2.y, h3.y));
            ub.x = hadd(hadd(u0.x, u1.x), hadd(u2.x, u3.x)); ub.y = hadd(hadd(u0.y, u1.y), hadd(u2.y, u3.y));
            const float d0 = ((s0 + p1.x) + p2.x) + p3.x, d1 = ((s1 + p1.y) + p2.y) + p3.y;
            bool bad;
            {
                const float f0 = ex2(d0), f1 = ex2(d1);
                const uint32_t pm = pack(f0, f1), pj = pack(f1, f0);
                FENCE();
                mma8(o[4], pm, pj, one2a); mma8(o[3], pm, pj, ub.w); mma8(o[2], pm, pj, ub.z); mma8(o[0], pm, pj, ub.x); mma8(o[1], pm, pj, ub.y);
                const float r = rcp(o[4][0]);
                bad = __float_as_uint(o[4][0]) - 0x2f800000u > 0x20000000u;
                red_bf16x8(g_ACC + (bad ? rdump : roff), pack(o[0][0] * r, o[0][1] * r), pack(o[1][0] * r, o[1][1] * r), pack(o[2][0] * r, o[2][1] * r),
                           __byte_perm(pack(o[3][0] * r, o[3][1] * r), CNT1, psel));
            }
            FENCE();
            const uint32_t t0 = clk();
            DBG(8);
            float de[16], dx[16];
            const uint64_t desc = (uint64_t)(((sb + R_ST2 + (s & 1) * XB) & 0x3FFFF) >> 4) | (1ull << 16) | (16ull << 32) | (3ull << 62);
            auto scores = [&](const uint4& q0, const uint4& q1, const uint4& q2, const uint4& q3) {
                wg_fence();
                wgmma32<0>(de, q0, desc, 0); wgmma32<0>(dx, q0, desc + 64, 0);
                wgmma32<0>(de, q1, desc + 128, 1); wgmma32<0>(dx, q1, desc + 192, 1);
                wgmma32<0>(de, q2, desc + 256, 1); wgmma32<0>(dx, q2, desc + 320, 1);
                wgmma32<0>(de, q3, desc + 384, 1);
                wg_commit();
            };
            scores(tq0, tq1, tq2, tq3);
            stsm4t(uba + (s & 3) * 2048, ub.x, ub.y, ub.z, ub.w);
            rbar += 8;
            pp = g_ACC + (roff - rdelta);
            roff += (s & 1) ? 128 : 16384 - 128;
            if (s < NSEG - 1) mbar_wait_nf(bar + B_KV + 8);
            wg_wait0();
#pragma unroll
            for (int r = 0; r < 4; r++) {
                sts32f(smt + (R_SXI - R_SMI) + r * 1024, de[4 * r] + dx[4 * r + 2]); sts32f(smt + (R_SXI - R_SMI) + r * 1024 + 32, de[4 * r + 1] + dx[4 * r + 3]);
            }
            bar_arrive<BR, 256>();
            {
                uint8_t* redp = (uint8_t*)pp + rdelta;
                if (__any_sync(0xffffffffu, bad)) {
                    float e[8];
#pragma unroll
                    for (int i = 0; i < 8; i++) e[i] = lds32f(sb + R_SMX + (i >> 1) * 256 + (i & 1) * 32 + ((l8 & 24) << 3) + ((l8 >> 3) & 28));
                    float m = fmaxf(d0, d1);
#pragma unroll
                    for (int i = 0; i < 8; i++) m = fmaxf(m, e[i]);
                    m = fmaxf(m, __shfl_xor_sync(0xffffffffu, m, 1)); m = fmaxf(m, __shfl_xor_sync(0xffffffffu, m, 2));
#pragma unroll
                    for (int i = 0; i < 8; i++) e[i] = ex2(e[i] - m);
                    const uint32_t pn = pack(ex2(d0 - m), ex2(d1 - m));
                    const uint4 ea = make_uint4(pack(e[0], e[1]), 0u, pack(e[2], e[3]), 0u), eb = make_uint4(pack(e[4], e[5]), 0u, pack(e[6], e[7]), 0u);
                    const uint4 u4 = ldsm4t(uba + (s & 3) * 2048);
                    const uint32_t uq[4] = {u4.x, u4.y, u4.z, u4.w};
#pragma unroll
                    for (int q = 0; q < 4; q++) {
                        const uint4 vb = ldsm4t(lw - w * 3584 + R_STG + S_V + stg + (q < 2 ? tl0 + q : (q == 2 ? tl2 : tl3)) * 512);
                        mmaz(o[q], ea, vb.x, vb.y); mma(o[q], eb, vb.z, vb.w); mma8(o[q], pn, 0u, uq[q]);
                    }
                    mmaz(o[4], ea, ONE2, ONE2); mma(o[4], eb, ONE2, ONE2); mma8(o[4], pn, 0u, ONE2);
                    const float r2 = rcp(o[4][0]);
                    if (bad) red_bf16x8(redp, pack(o[0][0] * r2, o[0][1] * r2), pack(o[1][0] * r2, o[1][1] * r2), pack(o[2][0] * r2, o[2][1] * r2),
                                        __byte_perm(pack(o[3][0] * r2, o[3][1] * r2), CNT1, psel));
                    __syncwarp();
                }
            }
            { const uint32_t ds = stg == (NST - 1) * STGB ? -(NST - 1) * STGB : STGB; stg += ds; vaA += ds; vaB += ds; kq += ds; }
            DBG(9);
            while ((int)(clk() - t0) < POLL_DELAY) {}
            v0 = ld_poll(pp); v1 = ld_poll(pp + 3 * 4096); v2 = ld_poll(pp + 4096); v3 = ld_poll(pp + 2 * 4096);
            bar_arrive<BL, 160>();
            FENCE();
            bar_sync<BS, 128>();
            {
                const uint32_t a = l8 + R_SXI + w * 1024, rw = mapa(sb, w);
                const float2 p0 = lds64f(a), p1 = lds64f(a + 256), p2 = lds64f(a + 512), p3 = lds64f(a + 768);
                sta2f(l8 + (rw - sb + R_LX + (s & 1) * 1024 + c * 256), rw + R_BAR + B_L1 + s * 8, (p0.x + p1.x) + (p2.x + p3.x), (p0.y + p1.y) + (p2.y + p3.y));
            }
            if (w == 3 && s < NSEG - 1) {
                if (elect()) tma2d(sb + R_BK, &maps.acc, ((s + 1) & 1) * 16, ((s + 1) >> 1) * 64, bar + B_BK + 8);
                __syncwarp();
            }
        }
        if (tid == 0) GT(0, 3);
        mbar_wait_nf(sb + R_BAR + B_BK + (NSEG - 1) * 8);
        asm volatile("cp.async.wait_all;" ::: "memory");
    } else {
        const int* flagp = g_FLAG + (lane == 2 ? 32 + 2 * h + (c >> 1) : 2 * h + (lane & 1)) * 64;
        if (w == 1) {
            wait_flag(flagp, 4);
            __syncwarp();
            asm volatile("fence.proxy.async.shared::cta; fence.proxy.async.global;" ::: "memory");
            if (elect()) { load_stage(sb, 0, 0, h, c, &maps.x); load_stage(sb, 1, STGB, h, c, &maps.x); }
            __syncwarp();
        }
        uint32_t pr[5];
        auto softmax = [&](int s, uint32_t stg) {
            const uint32_t a = l8 + R_LX + (s & 1) * 1024, x = l16 + R_STG + stg + S_XX;
            const float4 q0 = lds128f(x), q1 = lds128f(x + 1024), q2 = lds128f(x + 512), q3 = lds128f(x + 1536);
            const float2 p0 = lds64f(a), p1 = lds64f(a + 256), p2 = lds64f(a + 512), p3 = lds64f(a + 768);
            float v[10] = {q0.x + q1.x, q0.y + q1.y, q0.z + q1.z, q0.w + q1.w, q2.x + q3.x, q2.y + q3.y, q2.z + q3.z, q2.w + q3.w,
                           (p0.x + p1.x) + (p2.x + p3.x), (p0.y + p1.y) + (p2.y + p3.y)};
            const int lim = 8 * c + g - 2 * t;
#pragma unroll
            for (int i = 0; i < 8; i++) v[i] = (8 * (i >> 1) + (i & 1) <= lim) ? v[i] : -INFINITY;
            float m = fmaxf(fmaxf(fmaxf(fmaxf(v[0], v[1]), fmaxf(v[2], v[3])), fmaxf(fmaxf(v[4], v[5]), fmaxf(v[6], v[7]))), fmaxf(v[8], v[9]));
            m = fmaxf(m, __shfl_xor_sync(0xffffffffu, m, 1)); m = fmaxf(m, __shfl_xor_sync(0xffffffffu, m, 2));
            float l = 0.f;
#pragma unroll
            for (int i = 0; i < 10; i++) { v[i] = ex2(v[i] - m); l += v[i]; }
            l += __shfl_xor_sync(0xffffffffu, l, 1); l += __shfl_xor_sync(0xffffffffu, l, 2);
            const float r = rcp(l);
#pragma unroll
            for (int q = 0; q < 5; q++) pr[q] = pack(v[2 * q] * r, v[2 * q + 1] * r);
        };
        auto send_p = [&](int s) {
            const uint32_t r0 = mapa(sb, 0), rstride = mapa(sb, 1) - r0;
            const uint32_t a = r0 + R_PB + (s & 3) * 2176, b = r0 + R_BAR + B_L2 + s * 8;
#pragma unroll
            for (int q = 0; q < 4; q++) sta4(a + q * rstride + c * 512 + lane * 16, b + q * rstride, pr[4], pr[0], pr[1], pr[2]);
            if (c == 3) {
#pragma unroll
                for (int q = 0; q < 4; q++) sta1(a + q * rstride + 2048 + lane * 4, b + q * rstride, pr[3]);
            }
        };
        auto pv = [&](int s, uint32_t stg, int m0, bool third) {
            const uint32_t pa = R_PB + (s & 3) * 2176;
            const uint32_t va = sb + R_STG + stg + S_V + (lane & 7) * 16 + (lane & 8) * 64 + m0 * 1024, vb = va + 128 + (lane >> 4) * 128;
            const uint32_t ua = lane < 16 ? l16 + R_UB + (s & 3) * 2048 + m0 * 256 : va, ud = lane < 16 ? 256 : 1024;
            const uint32_t oa = sb + R_OUT + (s & 1) * 7168 + (lane & 7) * 112 + (lane >> 4) * 896;
            const int ot = 2 * m0 + ((lane >> 3) & 1);
            auto oaddr = [&](int tl) { return oa + tl * 16 + (tl >= 7 ? 3584 - 112 : 0); };
            const uint4 a0 = ldsm4t(ua), p3 = lds128(l16 + pa + 1536), p2 = lds128(l16 + pa + 1024), a1 = ldsm4t(vb), p1 = lds128(l16 + pa + 512);
            const uint2 p0 = lds64(l16 + pa);
            const uint4 a2 = ldsm4t(va + 384 + (lane >> 4) * 1024);
            const uint32_t p4 = lds32(sb + pa + 2048 + lane * 4);
            const uint4 b0 = ldsm4t(ua + ud), b1 = ldsm4t(vb + 1024);
            FENCE();
            auto tile = [&](const uint4& q0, const uint4& q1, uint32_t q2, uint32_t q3, uint32_t o) {
                float x[4][4];
                mmaz(x[3], q0, p3.x, p3.y); mmaz(x[2], q0, p2.x, p2.y); mmaz(x[1], q0, p1.x, p1.y); mmaz(x[0], q0, p0.x, p0.y);
                mma(x[3], q1, p3.z, p3.w); mma(x[2], q1, p2.z, p2.w); mma(x[1], q1, p1.z, p1.w);
                mma8(x[3], q2, q3, p4);
                stsm4t(o, pack(x[0][0], x[0][1]), pack(x[0][2], x[0][3]), pack(x[1][0], x[1][1]), pack(x[1][2], x[1][3]));
                stsm4t(o + 1792, pack(x[2][0], x[2][1]), pack(x[2][2], x[2][3]), pack(x[3][0], x[3][1]), pack(x[3][2], x[3][3]));
            };
            tile(a0, a1, a2.x, a2.y, oaddr(ot));
            if (third) {
                const uint4 c0 = ldsm4t(ua + 2 * ud), c1 = ldsm4t(vb + 2048);
                const uint2 c2 = ldsm2t(va + 384 + 2048);
                tile(b0, b1, a2.z, a2.w, oaddr(ot + 2));
                tile(c0, c1, c2.x, c2.y, oaddr(ot + 4));
            } else tile(b0, b1, a2.z, a2.w, oaddr(ot + 2));
        };
        const uint32_t ba = lw + R_MB, upa = l8 + R_UP + w * 1024;
        const uint32_t rdst = opq(rsb + R_SMX + c * 256 + lane * 8), edst = opq(rsb + R_SME + c * 128 + lane * 4);
        uint32_t rbar = opq(rsb + R_BAR + B_SM + (lw & 15)), ebar = opq(rsb + R_BAR + B_SX + (lw & 15));
        uint32_t stg2 = 2 * STGB, stgv = (NST - 2) * STGB;
#pragma unroll 1
        for (int s = 0; s < NSEG; s++) {
            uint4 w0[7];
#pragma unroll
            for (int m = 0; m < 7; m++) w0[m] = lds128v(lw + R_W0 + 14336 + m * 512);
            bar_sync<BX, 256>();
            const float2 p0 = lds64f(l8 + R_SXJ), p1 = lds64f(l8 + R_SXJ + 256), p2 = lds64f(l8 + R_SXJ + 512), p3 = lds64f(l8 + R_SXJ + 768);
            FENCE();
            const uint4 v0 = ldsm4(ba), v1 = ldsm4(ba + 512), v2 = ldsm4(ba + 1024);
            const uint2 v3 = ldsm2(ba + 1536);
            FENCE();
            {
                const float s0 = (p0.x + p1.x) + (p2.x + p3.x), s1 = (p0.y + p1.y) + (p2.y + p3.y);
                sta1(edst, ebar, pack(ex2(s0), ex2(s1)));
                sta2f(rdst, rbar, s0, s1);
            }
            DBG(21);
            float acc[7][4];
            const uint32_t b[14] = {v0.x, v0.y, v0.z, v0.w, v1.x, v1.y, v1.z, v1.w, v2.x, v2.y, v2.z, v2.w, v3.x, v3.y};
            bar_sync<BH, 256>();
            FENCE();
#pragma unroll
            for (int j = 0; j < 3; j++) { A(0, j); FENCE(); A(1, j); FENCE(); A(2, j); if (j < 2) FENCE(); }
            bar_sync<BG, 256>();
            FENCE();
            DBG(20);
            A(0, 3); A(1, 3); FENCE(); A(2, 3); A(3, 0); FENCE();
            A(0, 4); A(1, 4); FENCE(); A(2, 4); A(4, 0); FENCE();
            A(0, 5); A(1, 5); FENCE(); A(2, 5); A(5, 0); FENCE();
            A(0, 6); A(1, 6); FENCE(); A(2, 6); A(6, 0); FENCE();
            A(3, 1); A(4, 1); FENCE();
            A(5, 1); A(6, 1); sts64(upa, pack(acc[0][0], acc[0][1]), pack(acc[0][2], acc[0][3])); FENCE();
            A(3, 2); A(4, 2); sts64(upa + 256, pack(acc[1][0], acc[1][1]), pack(acc[0][2], acc[0][3])); sts64(upa + 512, pack(acc[2][0], acc[2][1]), pack(acc[2][2], acc[2][3])); FENCE();
            A(5, 2); A(6, 2); sts64(upa + 768, pack(acc[1][2], acc[1][3]), pack(acc[2][2], acc[2][3]));
            bar_arrive<BV, 256>(); FENCE();
#pragma unroll
            for (int j = 3; j < 7; j++) { A(3, j); A(4, j); A(5, j); A(6, j); FENCE(); }
#pragma unroll
            for (int m = 3; m < 7; m++) { sts64(upa + 4096 + (m - 3) * 256, pack(acc[m][0], acc[m][1]), pack(acc[m][2], acc[m][3])); if (m == 4) FENCE(); }
            bar_arrive<BU, 256>();
            DBG(22);
            if (w == 0) {
                if (s > 0) mbar_wait(sb + R_BAR + B_L1 + (s - 1) * 8, 0);
                bar_sync<BR, 256>();
                if (s > 0) { softmax(s - 1, stgv == (NST - 1) * STGB ? 0 : stgv + STGB); send_p(s - 1); }
            } else {
                if (s > 1) mbar_wait(sb + R_BAR + B_L2 + (s - 2) * 8, 0);
                int have = 0;
                const int* fp = flagp + ((s + 2) & 2) * 16;
                if (w == 1) {
                    asm volatile("cp.async.bulk.wait_group.read 0;" ::: "memory");
                    asm volatile("fence.proxy.async.shared::cta;" ::: "memory");
                    if (s > 0) mbar_wait_nf(sb + R_BAR + B_BK + s * 8);
                    if (!(s & 1)) have = ld_flag(fp);
                }
                if (w == 2 && blockIdx.x == 0 && lane == 0) st_flag(&g_FLAG[F_PROG * 32], s);
                bar_sync<BR, 256>();
                if (s > 1) pv(s - 2, stgv, 2 * w - 2, w == 3);
                if (w == 1) {
                    if (!(s & 1) && s + 2 < NSEG) {
                        int it = 0;
                        while (have < ((s + 2) | 3) + 1) { have = ld_flag(fp); if (++it > (1 << 20)) __trap(); }
                        __syncwarp();
                        asm volatile("fence.proxy.async.global;" ::: "memory");
                    }
                    bar_sync<BL, 160>();
                    FENCE();
                    const uint32_t t1 = clk(); while ((int)(clk() - t1) < TMA_DELAY) {}
                    if (elect()) {
                        if (s + 2 < NSEG) load_stage(sb, s + 2, stg2, h, c, &maps.x);
                        if (s > 2) tma_red2d(&maps.out, 8 + 2 * c, 32 * (s - 3), sb + R_OUT + ((s - 3) & 1) * 7168);
                    }
                    __syncwarp();
                }
            }
            DBG(24);
            stg2 = stg2 == (NST - 1) * STGB ? 0 : stg2 + STGB;
            stgv = stgv == (NST - 1) * STGB ? 0 : stgv + STGB;
            rbar += 8; ebar += 8;
        }
        if (w == 2 && lane == 0) retire(total);
        __syncwarp();
        if (w == 0) { mbar_wait(sb + R_BAR + B_L1 + (NSEG - 1) * 8, 0); softmax(NSEG - 1, ((NSEG - 1) % NST) * STGB); send_p(NSEG - 1); }
#pragma unroll 1
        for (int s = NSEG - 3; s < NSEG; s++) {
            if (s > NSEG - 3 && w > 0) { mbar_wait(sb + R_BAR + B_L2 + s * 8, 0); pv(s, (s % NST) * STGB, 2 * w - 2, w == 3); }
            asm volatile("fence.proxy.async.shared::cta;" ::: "memory");
            if (w == 1) asm volatile("cp.async.bulk.wait_group.read 0;" ::: "memory");
            bar_sync<BO, 128>();
            if (w == 1 && elect()) tma_red2d(&maps.out, 8 + 2 * c, 32 * s, sb + R_OUT + (s & 1) * 7168);
            __syncwarp();
        }
        if (w == 1) asm volatile("cp.async.bulk.wait_group 0;" ::: "memory");
        if (tid == 160) GT(0, 4);
    }
    cluster_sync();
}

constexpr int G_F = 0, G_BN = 86016, G_B = 114688;
constexpr int G_ST = 200704;
constexpr int G_BAR = 229376;
constexpr int G_SMEM = G_BAR + 64;

#define HANDK 13
#define COVER 7
__device__ __forceinline__ uint4 ldcg(const uint4* p) {
    uint4 v; asm volatile("ld.global.cg.v4.u32 {%0,%1,%2,%3},[%4];" : "=r"(v.x), "=r"(v.y), "=r"(v.z), "=r"(v.w) : "l"(p) : "memory"); return v;
}
__device__ __forceinline__ void proj_role(uint32_t sb, const __nv_bfloat16* __restrict__ wk, const Maps& maps) {
    const int tid = threadIdx.x, lane = tid & 31, wid = __shfl_sync(0xffffffffu, tid >> 5, 0), wg = wid >> 2, u = wid & 3;
    const int g = lane >> 2, t = lane & 3, mt = u & 1;
    const int n = blockIdx.x, M = n >> 5, h = (n >> 1) & 15, hf = n & 1;
    {
        if (tid == 0) {
#pragma unroll 1
            for (int e = 0; e < 4; e++) {
                mbar_init(sb + G_BAR + e * 8, 1);
                asm volatile("fence.mbarrier_init.release.cluster;" ::: "memory");
                mbar_expect(sb + G_BAR + e * 8, 28672);
                if (M == 0) tma2d(sb + G_B + e * 28672, &maps.q224, h * 256 + 64 * e, 224 * hf, sb + G_BAR + e * 8);
                else tma3d(sb + G_B + e * 28672, &maps.o224, 0, h * 256 + 64 * e, 7 * hf, sb + G_BAR + e * 8);
            }
        }
        const uint4* src = (const uint4*)(wk + (size_t)(64 * wg + 32 * (u >> 1) + 4 * (u & 1) + 8 * (lane >> 4) + ((lane >> 3) & 1)) * 4096 + h * 256) + (lane & 7);
        const uint32_t bw = sb + G_BN + wid * 2048 + (lane >> 3) * 128, br = sb + G_BN + wid * 2048 + (lane & 15) * 128;
        const uint64_t db = M == 0 ? mdesc(sb + G_B, 16, 1024, 1) : mdesc(sb + G_B, 4096, 512, 2);
        uint32_t fa = sb + G_F + (8 * wg + 2 * u) * 3584 + g * 64 + ((t ^ ((g >> 1) & 3)) << 4);
        const float sc = M ? 1.f : LOG2E / 16.f;
        uint4 a[16], q[14];
        auto load = [&]() {
#pragma unroll
            for (int k = 0; k < 16; k++) a[k] = ldcg(src + (16 * (k & 1) + (k & 2)) * 512 + 8 * (k >> 2));
            src += 128 * 512;
        };
        auto store = [&]() {
#pragma unroll
            for (int i = 0; i < 14; i++) sts128(fa + (i & 1) * 3584 + (i >> 1) * 512, q[i]);
            fa += 57344;
        };
        load();
#pragma unroll
        for (int i = 0; i < 14; i++) q[i] = make_uint4(0, 0, 0, 0);
        bar_sync(3, 256);
#pragma unroll 1
        for (int tile = wg; tile < 7; tile += 2) {
#pragma unroll
            for (int k = 0; k < 16; k += 4) {
#pragma unroll
                for (int i = 0; i < 4; i++) sts128(bw + i * 512 + (((lane & 7) ^ (4 * (i & 1) + (lane >> 3))) << 4), a[k + i]);
                __syncwarp();
#pragma unroll
                for (int i = 0; i < 4; i++) a[k + i] = ldsm4(br + (((2 * i + (lane >> 4)) ^ (lane & 7)) << 4));
                __syncwarp();
            }
            float d[112];
            GF(1, 4 + (tile >> 1));
            if (tile > 1) bar_sync(1 + wg, 256);
#pragma unroll
            for (int e = 0; e < 4; e++) {
                mbar_wait_nf(sb + G_BAR + e * 8);
                if (tile < 2) GF(1, e);
                if (M == 0) {
                    wg_fence();
#pragma unroll
                    for (int k = 0; k < 4; k++) wgmma224<0>(d, a[4 * e + k], db + ((e * 28672 + k * 32) >> 4), 4 * e + k);
                    wg_commit();
                } else {
                    wg_fence();
#pragma unroll
                    for (int k = 0; k < 4; k++) wgmma224<1>(d, a[4 * e + k], db + ((e * 28672 + k * 1024) >> 4), 4 * e + k);
                    wg_commit();
                }
            }
            if (tile > 0 && tile < 6) bar_arrive(2 - wg, 256);
            wg_wait<0>();
            GF(1, 8 + (tile >> 1));
            if (tile < 5) load();
            else {
                if (tid == 128) wait_flag(&g_FLAG[F_ZERO * 32], 512);
                bar_sync(3, 256);
                store();
            }
#pragma unroll
            for (int i = 0; i < 14; i++) {
                const float* e = d + 16 * (i >> 1) + 2 * (i & 1);
                q[i] = make_uint4(packv(e[0] * sc, e[1] * sc), packv(e[4] * sc, e[5] * sc), packv(e[8] * sc, e[9] * sc), packv(e[12] * sc, e[13] * sc));
            }
            if (tile < 3 || tile > 4) store();
        }
        asm volatile("fence.proxy.async.shared::cta;" ::: "memory");
    }
    uint4 a[28];
    const uint4* xp = g_XA + wid * 896 + lane;
    const int k0 = 14 * (1 - hf), k1 = 14 * hf;
    auto load = [&](int j0, const uint4* p) {
#pragma unroll
        for (int j = 0; j < 14; j++) a[j0 + j] = ldcg(p + j * 32);
    };
    load(0, xp + k0 * 32); load(14, xp + k1 * 32);
    bar_sync(3, 256);
    if (tid == 0) GT(1, 1);
    const uint64_t desc0 = mdesc(sb + G_F + k0 * 7168, 512, 3584, 2), desc1 = mdesc(sb + G_F + k1 * 7168, 512, 3584, 2);
    if (wg == 1) bar_arrive(1, 256);
    const uint4* xo = xp + 896 + k1 * 32;
    const uint32_t st0 = sb + G_ST + u * 7168 + t * 256 + ((g ^ (2 * t)) << 4), st1 = (st0 + 128) ^ 16;
    int prog = 0;
#pragma unroll 1
    for (int it = 0; it < 16; it++) {
        const int seg = 4 * it + 2 * wg + (u >> 1);
        float d[112];
        bar_sync(1 + wg, 256);
        wg_fence();
#pragma unroll
        for (int j = 0; j < 14; j++) wgmma224<1>(d, a[j], desc0 + j * (7168 >> 4), j);
        wg_commit();
#pragma unroll
        for (int j = 0; j < COVER; j++) wgmma224<1>(d, a[14 + j], desc1 + j * (7168 >> 4), true);
        wg_commit();
        const bool more = it < 15, other = M == 0 && mt == 0;
        xp += more ? 8 * 896 : 0;
        wg_wait<1>();
        load(0, other ? xo : xp + k0 * 32);
        xo += 8 * 896;
        wg_fence();
#pragma unroll
        for (int j = COVER; j < 14; j++) wgmma224<1>(d, a[14 + j], desc1 + j * (7168 >> 4), true);
        wg_commit();
        if (M == 1 && (wg == 0 || more)) bar_arrive(2 - wg, 256);
        const int ri = ((seg % RING) * 16 + h) * 4;
        wg_wait<0>();
        uint4 lo[7], hi[7];
#pragma unroll
        for (int q = 0; q < 7; q++) {
            const float* e = d + 16 * q;
            lo[q] = make_uint4(pack(e[0], e[1]), pack(e[4], e[5]), pack(e[8], e[9]), pack(e[12], e[13]));
            hi[q] = make_uint4(pack(e[2], e[3]), pack(e[6], e[7]), pack(e[10], e[11]), pack(e[14], e[15]));
        }
        float s0[4], s1[4], s2[4], s3[4];
        if (M == 0) {
            if (mt == 0) {
#pragma unroll
                for (int k = 0; k < 14; k++) {
                    const uint32_t l0 = (k & 1) ? lo[k >> 1].z : lo[k >> 1].x, l1 = (k & 1) ? lo[k >> 1].w : lo[k >> 1].y;
                    const uint32_t h0 = (k & 1) ? hi[k >> 1].z : hi[k >> 1].x, h1 = (k & 1) ? hi[k >> 1].w : hi[k >> 1].y;
                    if (k == 0) { mmaz(s0, a[14], l0, l1); mmaz(s1, a[14], h0, h1); mmaz(s2, a[0], l0, l1); mmaz(s3, a[0], h0, h1); }
                    else { mma(s0, a[14 + k], l0, l1); mma(s1, a[14 + k], h0, h1); mma(s2, a[k], l0, l1); mma(s3, a[k], h0, h1); }
                    if (k == HANDK) { FENCE(); if (wg == 0 || more) bar_arrive(2 - wg, 256); FENCE(); }
                }
            } else {
#pragma unroll
                for (int q = 0; q < 7; q++) {
                    const uint4 &a0 = a[14 + 2 * q], &a1 = a[15 + 2 * q];
                    if (q == 0) { mmaz(s0, a0, lo[q].x, lo[q].y); mmaz(s1, a0, hi[q].x, hi[q].y); mmaz(s2, a1, lo[q].z, lo[q].w); mmaz(s3, a1, hi[q].z, hi[q].w); }
                    else { mma(s0, a0, lo[q].x, lo[q].y); mma(s1, a0, hi[q].x, hi[q].y); mma(s2, a1, lo[q].z, lo[q].w); mma(s3, a1, hi[q].z, hi[q].w); }
                }
#pragma unroll
                for (int i = 0; i < 4; i++) { s2[i] += s0[i]; s3[i] += s1[i]; }
                FENCE();
                if (wg == 0 || more) bar_arrive(2 - wg, 256);
            }
        }
        if (it > 0 || wg == 1) bar_sync(4 + wg, 256);
#pragma unroll
        for (int q = 0; q < 7; q++) { sts128(st0 + q * 1024, lo[q]); sts128(st1 + q * 1024, hi[q]); }
        asm volatile("fence.proxy.async.shared::cta;" ::: "memory");
        __syncwarp();
        if (elect()) {
            if (M == 0) asm volatile("cp.async.bulk.tensor.3d.global.shared::cta.tile.bulk_group [%0,{%1,%2,%3}],[%4];"
                                     ::"l"(&maps.rk), "r"(0), "r"(ri + 2 * mt), "r"(28 * hf), "r"(sb + G_ST + u * 7168) : "memory");
            else asm volatile("cp.async.bulk.tensor.4d.global.shared::cta.tile.bulk_group [%0,{%1,%2,%3,%4}],[%5];"
                              ::"l"(&maps.rv), "r"(0), "r"(2 * mt), "r"(0), "r"(ri + 2 * hf), "r"(sb + G_ST + u * 7168) : "memory");
            asm volatile("cp.async.bulk.commit_group;" ::: "memory");
        }
        __syncwarp();
        int back = 0;
        if (M == 0) {
            float4* sp = (float4*)(g_REC + (size_t)ri * RECC + S_XX + hf * 1024 + mt * 512) + lane;
            sp[2 * RECC / 16] = make_float4(s2[0], s2[1], s3[0], s3[1]); sp[3 * RECC / 16] = make_float4(s2[2], s2[3], s3[2], s3[3]);
            if (mt == 0) {
                sp[0] = make_float4(s0[0], s0[1], s1[0], s1[1]); sp[RECC / 16] = make_float4(s0[2], s0[3], s1[2], s1[3]);
                back = ld_flag((const int*)sp) ^ ld_flag((const int*)(sp + RECC / 16));
                load(0, xp + k0 * 32);
            }
            back ^= ld_flag((const int*)(sp + 2 * RECC / 16)) ^ ld_flag((const int*)(sp + 3 * RECC / 16));
        }
        FENCE();
        load(14, xp + k1 * 32);
        FENCE();
        asm volatile("cp.async.bulk.wait_group.read 0;" ::: "memory");
        if (wg == 0 || more) bar_arrive(5 - wg, 256);
        back = __reduce_or_sync(0xffffffffu, (unsigned)back);
        if (elect()) {
            asm volatile("cp.async.bulk.wait_group 0; fence.proxy.async.global;" ::: "memory");
            asm volatile("red.relaxed.gpu.global.add.s32 [%0],%1;" ::"l"(g_FLAG + (n * 2 + wg) * 32), "r"(1 + (back & (int)(blockDim.y - 1))) : "memory");
        }
        __syncwarp();
        if (tid == 32 && it == 0) GT(1, 2);
        if (u == 3) {
            int i2 = 0;
            while (prog < seg + 5 - RING) { if (i2) __nanosleep(400); prog = ld_flag(&g_FLAG[F_PROG * 32]); if (++i2 > (1 << 18)) __trap(); }
        }
    }
}

struct PartA { const __nv_bfloat16 *lar, *aim, *cre, *cim, *ldt, *dsk; };
constexpr int C_PP = 4368, C_TP = 272, C_TW = 56 * C_TP;
constexpr int C_RAW = 0;
constexpr int C_PL = 32768;
constexpr int C_T = C_PL + 8 * C_PP;
constexpr int C_KS = 8320;
constexpr int C_BAR = C_T + 8 * C_TW, C_UNIT = C_BAR + 8;
static_assert(C_UNIT + 8 <= G_SMEM, "conv smem");

struct cpx { float r, i; };
__device__ __forceinline__ cpx cmul(cpx a, cpx b) { return {fmaf(a.r, b.r, -a.i * b.i), fmaf(a.r, b.i, a.i * b.r)}; }
__device__ __forceinline__ cpx cmulc(cpx a, cpx b) { return {fmaf(a.r, b.r, a.i * b.i), fmaf(a.i, b.r, -a.r * b.i)}; }
__device__ __forceinline__ cpx cexp(float er, float wi, float p) {
    const float e = ex2(er * p), x = wi * p;
    const float k = rintf(x * 0.15915494309189535f);
    const float r = fmaf(k, 1.7484555314695172e-07f, fmaf(k, -6.2831854820251465f, x));
    return {e * __cosf(r), e * __sinf(r)};
}
__device__ __forceinline__ uint32_t lds16(uint32_t a) { uint32_t k; asm volatile("{.reg .u16 h; ld.shared.u16 h,[%1]; cvt.u32.u16 %0,h;}" : "=r"(k) : "r"(a) : "memory"); return k; }
__device__ __forceinline__ float rbf(float x) { return __bfloat162float(__float2bfloat16(x)); }

__device__ __forceinline__ void kgen(uint32_t tb, int d, const PartA& A) {
    const int lane = threadIdx.x & 31, g = lane >> 2, t = lane & 3;
    uint4 la = __ldg((const uint4*)(A.lar + d * NST8) + lane), ai = __ldg((const uint4*)(A.aim + d * NST8) + lane);
    uint4 cr = __ldg((const uint4*)(A.cre + d * NST8) + lane), ci = __ldg((const uint4*)(A.cim + d * NST8) + lane);
    const float dt = rbf(expf(__bfloat162float(A.ldt[d])));
    float acc[2][3][4];
#pragma unroll
    for (int i = 0; i < 6; i++) acc[i / 3][i % 3][0] = acc[i / 3][i % 3][1] = acc[i / 3][i % 3][2] = acc[i / 3][i % 3][3] = 0.f;
    const uint32_t wa = tb + lane * 8, ra = tb + (lane & 15) * C_TP + (lane >> 4) * 16, rb = tb + (32 + (lane & 7)) * C_TP + (lane >> 3) * 16;
#pragma unroll 1
    for (int it = 0; it < 4; it++) {
        cpx c[2], w1[2], w2[2], w4[2], w8[2], w256[2], y[2][4];
#pragma unroll
        for (int z = 0; z < 2; z++) {
            auto half = [&](uint32_t v) { return __uint_as_float(z ? v & 0xffff0000u : v << 16); };
            const float er = (-rbf(expf(half(la.x))) * dt) * LOG2E, wi = half(ai.x) * dt;
            c[z] = {2.f * (half(cr.x) * dt), -2.f * (half(ci.x) * dt)};
            w1[z] = cexp(er, wi, 1.f); y[z][1] = cexp(er, wi, 64.f);
            w2[z] = cmul(w1[z], w1[z]); w4[z] = cmul(w2[z], w2[z]); w8[z] = cmul(w4[z], w4[z]);
            y[z][0] = {1.f, 0.f}; y[z][2] = cmul(y[z][1], y[z][1]); y[z][3] = cmul(y[z][2], y[z][1]); w256[z] = cmul(y[z][2], y[z][2]);
        }
        la = make_uint4(la.y, la.z, la.w, 0); ai = make_uint4(ai.y, ai.z, ai.w, 0); cr = make_uint4(cr.y, cr.z, cr.w, 0); ci = make_uint4(ci.y, ci.z, ci.w, 0);
        __syncwarp();
        auto put = [&](int row, cpx a, cpx b) { sts64(wa + row * C_TP, pack(a.r, a.i), pack(b.r, b.i)); };
#pragma unroll
        for (int k = 0; k < 8; k++)
#pragma unroll
            for (int j = 0; j < 4; j++) {
                put(8 * j + k, y[0][j], y[1][j]);
                if (k < 7) { y[0][j] = (k == 0 && j == 0) ? w8[0] : cmul(y[0][j], w8[0]); y[1][j] = (k == 0 && j == 0) ? w8[1] : cmul(y[1][j], w8[1]); }
            }
        cpx x0 = c[0], x1 = c[1], z0 = c[0], z1 = c[1];
        put(32, x0, x1);
#pragma unroll
        for (int k = 1; k < 9; k++) {
            if (k < 8) { x0 = cmulc(x0, w1[0]); x1 = cmulc(x1, w1[1]); put(32 + k, x0, x1); }
            z0 = cmulc(z0, w256[0]); z1 = cmulc(z1, w256[1]);
            put(k == 1 ? 40 : (k < 4 ? 40 + 2 * k : 44 + k), z0, z1);
            if (k == 1) {
                const cpx p0 = cmulc(z0, w4[0]), p1 = cmulc(z1, w4[1]);
                put(41, cmulc(z0, w2[0]), cmulc(z1, w2[1])); put(42, p0, p1); put(43, cmulc(p0, w2[0]), cmulc(p1, w2[1]));
            } else if (k < 4) put(41 + 2 * k, cmulc(z0, w4[0]), cmulc(z1, w4[1]));
        }
        __syncwarp();
#pragma unroll
        for (int kp = 0; kp < 4; kp++) {
            const uint4 b0 = ldsm4(rb + kp * 64), b1 = ldsm4(rb + 8 * C_TP + kp * 64), b2 = ldsm4(rb + 16 * C_TP + kp * 64);
#pragma unroll
            for (int m = 0; m < 2; m++) {
                const uint4 a0 = ldsm4(ra + m * 16 * C_TP + kp * 64), a1 = ldsm4(ra + m * 16 * C_TP + kp * 64 + 32);
                mma(acc[m][0], a0, b0.x, b0.y); mma(acc[m][1], a0, b1.x, b1.y); mma(acc[m][2], a0, b2.x, b2.y);
                mma(acc[m][0], a1, b0.z, b0.w); mma(acc[m][1], a1, b1.z, b1.w); mma(acc[m][2], a1, b2.z, b2.w);
            }
        }
    }
    __syncwarp();
    const uint32_t ks = tb + C_KS;
    const int o1 = t < 2 ? 256 + 4 * t : 256 * t, e1 = t < 2 ? 2 : 4;
#pragma unroll
    for (int q = 0; q < 4; q++) {
        const uint32_t a = ks + 16 * (8 * q + g);
        const float* v0 = acc[q >> 1][0] + 2 * (q & 1); const float* v1 = acc[q >> 1][1] + 2 * (q & 1); const float* v2 = acc[q >> 1][2] + 2 * (q & 1);
        const uint32_t p1 = pack(v1[0], v1[1]), p2 = pack(v2[0], v2[1]);
        sts32(a + 4 * t, pack(v0[0], v0[1]));
        asm volatile("st.shared.u16 [%0],%1;" ::"r"(a + 2 * o1), "h"((uint16_t)p1) : "memory");
        asm volatile("st.shared.u16 [%0],%1;" ::"r"(a + 2 * (o1 + e1)), "h"((uint16_t)(p1 >> 16)) : "memory");
        if (t < 3) asm volatile("st.shared.u16 [%0],%1;" ::"r"(a + 2048 + 1024 * t), "h"((uint16_t)p2) : "memory");
        if (t < 2) asm volatile("st.shared.u16 [%0],%1;" ::"r"(a + 2560 + 1024 * t), "h"((uint16_t)(p2 >> 16)) : "memory");
    }
    __syncwarp();
    auto W = [](uint32_t lo, uint32_t hi) { return __byte_perm(lo, hi, 0x5410); };
    const uint32_t r = tb + 64;
    if (lane < 16) sts32(tb + lane * 4, 0u);
    {
        const uint4 v = lds128(ks + lane * 16);
        const uint32_t pv = lane ? lds32(ks + lane * 16 - 4) : 0u;
        sts128(r + lane * 32, __byte_perm(v.x, pv, 0x7610), __byte_perm(v.x, 0, 0x1032), __byte_perm(v.y, v.x, 0x7610), __byte_perm(v.y, 0, 0x1032));
        sts128(r + lane * 32 + 16, __byte_perm(v.z, v.y, 0x7610), __byte_perm(v.z, 0, 0x1032), __byte_perm(v.w, v.z, 0x7610), __byte_perm(v.w, 0, 0x1032));
    }
    {
        const uint4 v = lds128(ks + 512 + lane * 16);
        const uint32_t c8 = lds32(ks + 528 + lane * 16), pv = lane ? v.x : lds16(ks + 510);
        sts128(r + 1024 + lane * 32, W(v.x, pv), W(v.x, v.x), W(v.y, v.x), W(v.z, v.y));
        sts128(r + 1040 + lane * 32, W(v.z, v.z), W(v.z, v.z), W(v.w, v.z), W(c8, v.w));
    }
    {
        const uint4 v = lds128(ks + 1024 + lane * 32), u = lds128(ks + 1040 + lane * 32);
        const uint32_t c0 = v.x, c4 = v.z, c8 = u.x, c12 = u.z, c16 = lds32(ks + 1056 + lane * 32), a = r + 2048 + lane * 64;
        sts128(a, W(c0, c0), W(c0, c0), W(c0, c0), W(c4, c0)); sts128(a + 16, W(c4, c4), W(c4, c4), W(c8, c4), W(c8, c8));
        sts128(a + 32, W(c8, c8), W(c8, c8), W(c8, c8), W(c12, c8)); sts128(a + 48, W(c12, c12), W(c12, c12), W(c16, c12), W(c16, c16));
    }
#pragma unroll
    for (int i = 0; i < 2; i++) {
        const uint32_t p = ks + 2048 + i * 1024 + lane * 32, a = r + 4096 + i * 2048 + lane * 64;
        const uint32_t c0 = lds32(p), c8 = lds32(p + 16), c16 = lds32(p + 32), aa = W(c0, c0), bb = W(c8, c8), cc = W(c16, c16);
        sts128(a, aa, aa, aa, aa); sts128(a + 16, aa, W(c8, c0), bb, bb); sts128(a + 32, bb, bb, bb, bb); sts128(a + 48, W(c16, c8), cc, cc, cc);
    }
}

__device__ __forceinline__ void stsm4(uint32_t a, const uint4& v) {
    asm volatile("stmatrix.sync.aligned.m8n8.x4.shared.b16 [%0],{%1,%2,%3,%4};" ::"r"(a), "r"(v.x), "r"(v.y), "r"(v.z), "r"(v.w) : "memory");
}
__device__ __forceinline__ uint32_t hmul(uint32_t a, uint32_t b) { uint32_t r; asm("mul.rn.bf16x2 %0,%1,%2;" : "=r"(r) : "r"(a), "r"(b)); return r; }

__device__ __forceinline__ void conv_role(uint32_t sb, const PartA& A, const Maps& maps, int total) {
    const int tid = threadIdx.x, lane = tid & 31, ch = __shfl_sync(0xffffffffu, tid >> 5, 0);
    const int g = lane >> 2, t = lane & 3;
    __syncthreads();
    if (tid == 0) { mbar_init(sb + C_BAR, 1); asm volatile("fence.mbarrier_init.release.cluster; fence.proxy.async.shared::cta;" ::: "memory"); }
    if (lane < 16) sts128(sb + C_PL + ch * C_PP + (lane >> 3) * 2176 + (lane & 7) * 16, 0u, 0u, 0u, 0u);
    const uint32_t raw = sb + C_RAW + ch * 4096 + lane * 16;
    const uint32_t pla = sb + C_PL + (lane & 7) * C_PP + ((lane >> 3) & 1) * 2176 + (8 + 16 * ch + (lane >> 4)) * 16;
    const uint32_t own = sb + C_PL + ch * C_PP + ((lane >> 3) & 1) * 2176 + (8 + 8 * (lane >> 4) + (lane & 7)) * 16;
#pragma unroll 1
    for (int round = 0;; round++) {
        if (tid == 0) sts32(sb + C_UNIT, (uint32_t)atomicAdd(&g_FLAG[F_WORK * 32], 1));
        asm volatile("cp.async.bulk.wait_group.read 0;" ::: "memory");
        __syncthreads();
        const int unit = (int)lds32(sb + C_UNIT);
        if (unit >= D / 8) break;
        if (elect()) {
            if (ch == 0) mbar_expect(sb + C_BAR, 32768);
            tma2d(sb + C_RAW + ch * 4096, &maps.u8, 8 * unit, 256 * ch, sb + C_BAR);
        }
        __syncwarp();
        const uint32_t dk = __ldg((const uint32_t*)(A.dsk + 8 * unit) + t);
        kgen(sb + C_T + ch * C_TW, 8 * unit + ch, A);
        mbar_wait(sb + C_BAR, round & 1);
#pragma unroll
        for (int i = 0; i < 8; i++) stsm4(pla + i * 32, ldsm4t(raw + i * 512));
        __syncthreads();
        float acc[16][4];
#pragma unroll
        for (int i = 0; i < 16; i++) acc[i][0] = acc[i][1] = acc[i][2] = acc[i][3] = 0.f;
        const uint32_t ra0 = sb + C_T + ch * C_TW + 64 + (g - 2 * t) * 4, rb0 = __shfl_sync(0xffffffffu, ra0, lane);
#pragma unroll 1
        for (int jj = 0; jj < 8; jj++) {
            uint4 win[8];
#pragma unroll
            for (int q = 0; q < 8; q++) win[q] = ldsm4(own - jj * 16 + q * 256);
            const uint32_t ra = ra0 + jj * 64, rb = rb0 + jj * 64;
#pragma unroll
            for (int m = 15; m >= 0; m--) {
                const uint4 a = make_uint4(lds32(ra + m * 512), lds32(ra + m * 512 + 32), lds32(ra + m * 512 - 32), lds32(rb + m * 512));
#pragma unroll
                for (int i = m; i < 16; i++) {
                    const uint4& w = win[(i - m) >> 1];
                    if ((i - m) & 1) mma(acc[i], a, w.z, w.w); else mma(acc[i], a, w.x, w.y);
                }
            }
        }
        __syncwarp();
#pragma unroll
        for (int q = 0; q < 8; q++)
            stsm4t(own + q * 256, pack(acc[2 * q][0], acc[2 * q][1]), pack(acc[2 * q][2], acc[2 * q][3]), pack(acc[2 * q + 1][0], acc[2 * q + 1][1]), pack(acc[2 * q + 1][2], acc[2 * q + 1][3]));
        __syncthreads();
#pragma unroll
        for (int i = 0; i < 8; i++) {
            const uint4 y = ldsm4t(pla + i * 32), v = ldsm4(raw + i * 512);
            stsm4(raw + i * 512, make_uint4(hadd(y.x, hmul(v.x, dk)), hadd(y.y, hmul(v.y, dk)), hadd(y.z, hmul(v.z, dk)), hadd(y.w, hmul(v.w, dk))));
        }
        asm volatile("fence.proxy.async.shared::cta;" ::: "memory");
        __syncwarp();
        if (elect()) {
            asm volatile("cp.async.bulk.tensor.2d.global.shared::cta.tile.bulk_group [%0,{%1,%2}],[%3];" ::"l"(&maps.o8), "r"(8 * unit), "r"(256 * ch), "r"(sb + C_RAW + ch * 4096) : "memory");
            asm volatile("cp.async.bulk.commit_group;" ::: "memory");
        }
        __syncwarp();
    }
    if (tid == 0) retire(total);
    asm volatile("cp.async.bulk.wait_group 0;" ::: "memory");
}

__global__ void __launch_bounds__(256, 1)
k_bulk(const __nv_bfloat16* __restrict__ wk, const __nv_bfloat16* __restrict__ wv, const PartA A, const __grid_constant__ Maps maps, int total) {
    extern __shared__ __align__(1024) uint8_t smem[];
    const uint32_t sb = smem_u32(smem);
    const int n = blockIdx.x, tid = threadIdx.x;
    if (tid == 0) GT(1, 0);
    if (tid < 6) asm volatile("prefetch.tensormap [%0];" ::"l"(&maps.q224 + tid) : "memory");
    if (n < 64) proj_role(sb, n < 32 ? wk : wv, maps);
    if (tid == 0) GT(1, 3);
    conv_role(sb, A, maps, total);
    if (tid == 0) GT(1, 4);
}

}

extern "C" void kernel_launch(void* const* d_in, const int* in_sizes, int n_in, void* d_out, int out_size) {
    typedef const __nv_bfloat16* P;
    const PartA A = {(P)d_in[1], (P)d_in[2], (P)d_in[3], (P)d_in[4], (P)d_in[5], (P)d_in[6]};
    const P x = (P)d_in[7], mem0 = (P)d_in[8], wq = (P)d_in[9], wk = (P)d_in[10], wv = (P)d_in[11], wo = (P)d_in[12];
    typedef CUresult (*EncodeFn)(CUtensorMap*, CUtensorMapDataType, cuuint32_t, void*, const cuuint64_t*, const cuuint64_t*, const cuuint32_t*,
                                 const cuuint32_t*, CUtensorMapInterleave, CUtensorMapSwizzle, CUtensorMapL2promotion, CUtensorMapFloatOOBfill);
    static EncodeFn encode = nullptr;
    static int nsm = 0;
    constexpr int RS = R_SMEM;
    if (!encode) {
        cudaFuncSetAttribute(k_rec, cudaFuncAttributeMaxDynamicSharedMemorySize, RS);
        cudaFuncSetAttribute(k_bulk, cudaFuncAttributeMaxDynamicSharedMemorySize, G_SMEM);
        int dev = 0; cudaGetDevice(&dev);
        cudaDeviceGetAttribute(&nsm, cudaDevAttrMultiProcessorCount, dev);
        cudaDriverEntryPointQueryResult qr;
        cudaGetDriverEntryPoint("cuTensorMapEncodeTiled", (void**)&encode, cudaEnableDefault, &qr);
    }
    struct U4 { cuuint64_t v[4]; };
    auto make = [&](CUtensorMap& m, CUtensorMapDataType ty, int rank, const void* p, U4 dims, U4 strides, U4 box, CUtensorMapSwizzle sw, CUtensorMapL2promotion pr) {
        const cuuint32_t b[4] = {(cuuint32_t)box.v[0], (cuuint32_t)box.v[1], (cuuint32_t)box.v[2], (cuuint32_t)box.v[3]}, es[4] = {1, 1, 1, 1};
        encode(&m, ty, rank, (void*)p, dims.v, strides.v, b, es, CU_TENSOR_MAP_INTERLEAVE_NONE, sw, pr, CU_TENSOR_MAP_FLOAT_OOB_FILL_NONE);
    };
    const CUtensorMapDataType BF = CU_TENSOR_MAP_DATA_TYPE_BFLOAT16;
    const CUtensorMapL2promotion P0 = CU_TENSOR_MAP_L2_PROMOTION_NONE, P2 = CU_TENSOR_MAP_L2_PROMOTION_L2_256B;
    void* acc; cudaGetSymbolAddress(&acc, g_ACC);
    Maps maps;
    make(maps.x, BF, 3, x, {16, S, 28}, {D * 2, 32}, {16, 32, 7}, CU_TENSOR_MAP_SWIZZLE_32B, P0);
    make(maps.out, BF, 3, d_out, {56, S, 16}, {OUTW * 2, 112}, {56, 32, 2}, CU_TENSOR_MAP_SWIZZLE_NONE, P0);
    make(maps.acc, CU_TENSOR_MAP_DATA_TYPE_UINT64, 2, acc, {32, 33 * 64}, {256}, {16, 64}, CU_TENSOR_MAP_SWIZZLE_NONE, P0);
    make(maps.q112, BF, 2, wq, {4096, D}, {8192}, {64, 112}, CU_TENSOR_MAP_SWIZZLE_128B, P2);
    make(maps.q224, BF, 2, wq, {4096, D}, {8192}, {64, 224}, CU_TENSOR_MAP_SWIZZLE_128B, P2);
    make(maps.o112, BF, 3, wo, {16, 4096, 28}, {D * 2, 32}, {16, 64, 7}, CU_TENSOR_MAP_SWIZZLE_32B, P2);
    make(maps.o224, BF, 3, wo, {32, 4096, 14}, {D * 2, 64}, {32, 64, 7}, CU_TENSOR_MAP_SWIZZLE_64B, P2);
    make(maps.k8, BF, 4, wk, {64, 8, 64, 56}, {8192, 128, 65536}, {64, 8, 2, 2}, CU_TENSOR_MAP_SWIZZLE_128B, P2);
    make(maps.v8, BF, 4, wv, {64, 8, 64, 56}, {8192, 128, 65536}, {64, 8, 2, 2}, CU_TENSOR_MAP_SWIZZLE_128B, P2);
    make(maps.u8, BF, 2, d_in[0], {D, S}, {D * 2}, {8, 256}, CU_TENSOR_MAP_SWIZZLE_NONE, P0);
    make(maps.o8, BF, 2, d_out, {OUTW, S}, {OUTW * 2}, {8, 256}, CU_TENSOR_MAP_SWIZZLE_NONE, P0);
    void* rec; cudaGetSymbolAddress(&rec, g_REC);
    make(maps.rk, CU_TENSOR_MAP_DATA_TYPE_UINT64, 3, rec, {16, RING * 64, 56}, {RECC, 128}, {16, 2, 28}, CU_TENSOR_MAP_SWIZZLE_128B, P0);
    make(maps.rv, CU_TENSOR_MAP_DATA_TYPE_UINT64, 4, (uint8_t*)rec + S_V, {16, 4, 14, RING * 64}, {128, 512, RECC}, {16, 2, 14, 2}, CU_TENSOR_MAP_SWIZZLE_128B, P0);
    k_rec<<<64, 256, RS, cudaStreamPerThread>>>(mem0, x, maps, nsm);
    cudaLaunchAttribute pdl[1];
    pdl[0].id = cudaLaunchAttributeProgrammaticStreamSerialization;
    pdl[0].val.programmaticStreamSerializationAllowed = 1;
    cudaLaunchConfig_t cfg = {};
    cfg.stream = cudaStreamPerThread;
    cfg.attrs = pdl; cfg.numAttrs = 1;
    cfg.gridDim = dim3(nsm - 64); cfg.blockDim = dim3(256); cfg.dynamicSmemBytes = G_SMEM;
    cudaLaunchKernelEx(&cfg, k_bulk, wk, wv, A, maps, nsm);
}
```

```cpp
#include <cuda.h>
#include <cuda_runtime.h>
#include <cuda_bf16.h>
#include <stdint.h>
#include <string.h>

namespace {

constexpr int D = 448, S = 2048, NSEG = 64, OUTW = 896, NST8 = 256;
#define RING 16
constexpr int RECC = 16384, RECB = 4 * RECC;
#define ALIAS 8
__device__ __align__(1024) uint8_t g_REC[(size_t)ALIAS * 16 * RECB + 64 * 200704];
#define g_FI (g_REC + (size_t)ALIAS * 16 * RECB)
static_assert((RING - ALIAS) * 16 * RECB <= 64 * 200704, "ring");
__device__ __align__(16384) uint8_t g_ACC[5 * 16384];
__device__ __align__(512) uint4 g_XA[128 * 28 * 32];
constexpr int F_IMG = 128, F_ZERO = 192, F_PROG = 193, F_WORK = 194, F_XA = 195, F_DONE = 196;
__device__ __align__(128) int g_FLAG[197 * 32];
#define GT(k, i)
#define GF(k, i)
#define GE(k, i)

__device__ __forceinline__ uint32_t smem_u32(const void* p) { return (uint32_t)__cvta_generic_to_shared(p); }
__device__ __forceinline__ void mma(float* c, const uint4& a, uint32_t b0, uint32_t b1) {
    asm volatile("mma.sync.aligned.m16n8k16.row.col.f32.bf16.bf16.f32 {%0,%1,%2,%3},{%4,%5,%6,%7},{%8,%9},{%0,%1,%2,%3};"
                 : "+f"(c[0]), "+f"(c[1]), "+f"(c[2]), "+f"(c[3]) : "r"(a.x), "r"(a.y), "r"(a.z), "r"(a.w), "r"(b0), "r"(b1));
}
__device__ __forceinline__ void mmaz(float* c, const uint4& a, uint32_t b0, uint32_t b1) {
    asm volatile("mma.sync.aligned.m16n8k16.row.col.f32.bf16.bf16.f32 {%0,%1,%2,%3},{%4,%5,%6,%7},{%8,%9},{%10,%10,%10,%10};"
                 : "=f"(c[0]), "=f"(c[1]), "=f"(c[2]), "=f"(c[3]) : "r"(a.x), "r"(a.y), "r"(a.z), "r"(a.w), "r"(b0), "r"(b1), "f"(0.f));
}
__device__ __forceinline__ void mma8(float* c, uint32_t a0, uint32_t a1, uint32_t b0) {
    asm volatile("mma.sync.aligned.m16n8k8.row.col.f32.bf16.bf16.f32 {%0,%1,%2,%3},{%4,%5},{%6},{%0,%1,%2,%3};"
                 : "+f"(c[0]), "+f"(c[1]), "+f"(c[2]), "+f"(c[3]) : "r"(a0), "r"(a1), "r"(b0));
}
__device__ __forceinline__ uint32_t pack(float lo, float hi) { uint32_t r; asm("cvt.rn.bf16x2.f32 %0,%1,%2;" : "=r"(r) : "f"(hi), "f"(lo)); return r; }
__device__ __forceinline__ uint32_t movm(uint32_t a) { uint32_t d; asm volatile("movmatrix.sync.aligned.m8n8.trans.b16 %0,%1;" : "=r"(d) : "r"(a)); return d; }
__device__ __forceinline__ uint4 ldsm4(uint32_t a) {
    uint4 r; asm volatile("ldmatrix.sync.aligned.m8n8.x4.shared.b16 {%0,%1,%2,%3},[%4];" : "=r"(r.x), "=r"(r.y), "=r"(r.z), "=r"(r.w) : "r"(a) : "memory"); return r;
}
__device__ __forceinline__ uint4 ldsm4t(uint32_t a) {
    uint4 r; asm volatile("ldmatrix.sync.aligned.m8n8.x4.trans.shared.b16 {%0,%1,%2,%3},[%4];" : "=r"(r.x), "=r"(r.y), "=r"(r.z), "=r"(r.w) : "r"(a) : "memory"); return r;
}
__device__ __forceinline__ uint2 ldsm2(uint32_t a) {
    uint2 r; asm volatile("ldmatrix.sync.aligned.m8n8.x2.shared.b16 {%0,%1},[%2];" : "=r"(r.x), "=r"(r.y) : "r"(a) : "memory"); return r;
}
__device__ __forceinline__ void wg_fence() { asm volatile("wgmma.fence.sync.aligned;" ::: "memory"); }
__device__ __forceinline__ void wg_commit() { asm volatile("wgmma.commit_group.sync.aligned;" ::: "memory"); }
__device__ __forceinline__ void wg_wait0() { asm volatile("wgmma.wait_group.sync.aligned 0;" ::: "memory"); }
__device__ __forceinline__ uint2 ldsm2t(uint32_t a) {
    uint2 r; asm volatile("ldmatrix.sync.aligned.m8n8.x2.trans.shared.b16 {%0,%1},[%2];" : "=r"(r.x), "=r"(r.y) : "r"(a) : "memory"); return r;
}
__device__ __forceinline__ void stsm4t(uint32_t a, uint32_t x, uint32_t y, uint32_t z, uint32_t w) {
    asm volatile("stmatrix.sync.aligned.m8n8.x4.trans.shared.b16 [%0],{%1,%2,%3,%4};" ::"r"(a), "r"(x), "r"(y), "r"(z), "r"(w) : "memory");
}
__device__ __forceinline__ void stsm2(uint32_t a, uint32_t x, uint32_t y) {
    asm volatile("stmatrix.sync.aligned.m8n8.x2.shared.b16 [%0],{%1,%2};" ::"r"(a), "r"(x), "r"(y) : "memory");
}
__device__ __forceinline__ float lds32f(uint32_t a) { float v; asm volatile("ld.shared.f32 %0,[%1];" : "=f"(v) : "r"(a) : "memory"); return v; }
__device__ __forceinline__ uint4 lds128(uint32_t a) {
    uint4 v; asm volatile("ld.shared.v4.u32 {%0,%1,%2,%3},[%4];" : "=r"(v.x), "=r"(v.y), "=r"(v.z), "=r"(v.w) : "r"(a) : "memory"); return v;
}
__device__ __forceinline__ float4 lds128f(uint32_t a) {
    float4 v; asm volatile("ld.shared.v4.f32 {%0,%1,%2,%3},[%4];" : "=f"(v.x), "=f"(v.y), "=f"(v.z), "=f"(v.w) : "r"(a) : "memory"); return v;
}
__device__ __forceinline__ uint4 lds128v(uint32_t a) {
    uint4 v; asm volatile("ld.volatile.shared.v4.u32 {%0,%1,%2,%3},[%4];" : "=r"(v.x), "=r"(v.y), "=r"(v.z), "=r"(v.w) : "r"(a) : "memory"); return v;
}
__device__ __forceinline__ uint2 lds64v(uint32_t a) { uint2 v; asm volatile("ld.volatile.shared.v2.u32 {%0,%1},[%2];" : "=r"(v.x), "=r"(v.y) : "r"(a) : "memory"); return v; }
__device__ __forceinline__ uint2 lds64(uint32_t a) { uint2 v; asm volatile("ld.shared.v2.u32 {%0,%1},[%2];" : "=r"(v.x), "=r"(v.y) : "r"(a) : "memory"); return v; }
__device__ __forceinline__ float2 lds64f(uint32_t a) { float2 v; asm volatile("ld.shared.v2.f32 {%0,%1},[%2];" : "=f"(v.x), "=f"(v.y) : "r"(a) : "memory"); return v; }
__device__ __forceinline__ uint32_t lds32(uint32_t a) { uint32_t v; asm volatile("ld.shared.u32 %0,[%1];" : "=r"(v) : "r"(a) : "memory"); return v; }
__device__ __forceinline__ void sts128(uint32_t a, uint32_t x, uint32_t y, uint32_t z, uint32_t w) {
    asm volatile("st.shared.v4.u32 [%0],{%1,%2,%3,%4};" ::"r"(a), "r"(x), "r"(y), "r"(z), "r"(w) : "memory");
}
__device__ __forceinline__ void sts128(uint32_t a, const uint4& v) { sts128(a, v.x, v.y, v.z, v.w); }
__device__ __forceinline__ void sts64f(uint32_t a, float x, float y) { asm volatile("st.shared.v2.f32 [%0],{%1,%2};" ::"r"(a), "f"(x), "f"(y) : "memory"); }
__device__ __forceinline__ void sts64(uint32_t a, uint32_t x, uint32_t y) { asm volatile("st.shared.v2.u32 [%0],{%1,%2};" ::"r"(a), "r"(x), "r"(y) : "memory"); }
__device__ __forceinline__ void sts32f(uint32_t a, float x) { asm volatile("st.shared.f32 [%0],%1;" ::"r"(a), "f"(x) : "memory"); }
#define CLUSTER 4
__device__ __forceinline__ uint32_t mapa(uint32_t a, uint32_t r) { uint32_t o; asm("mapa.shared::cluster.u32 %0,%1,%2;" : "=r"(o) : "r"(a), "r"(r + (blockIdx.x & (CLUSTER - 4)))); return o; }
__device__ __forceinline__ void sta4(uint32_t dst, uint32_t bar, uint32_t x, uint32_t y, uint32_t z, uint32_t w) {
    asm volatile("st.async.weak.shared::cluster.mbarrier::complete_tx::bytes.v4.b32 [%0],{%1,%2,%3,%4},[%5];" ::"r"(dst), "r"(x), "r"(y), "r"(z), "r"(w), "r"(bar) : "memory");
}
__device__ __forceinline__ void sta4f(uint32_t dst, uint32_t bar, const float4& v) { sta4(dst, bar, __float_as_uint(v.x), __float_as_uint(v.y), __float_as_uint(v.z), __float_as_uint(v.w)); }
__device__ __forceinline__ void sta2f(uint32_t dst, uint32_t bar, float x, float y) {
    asm volatile("st.async.weak.shared::cluster.mbarrier::complete_tx::bytes.v2.f32 [%0],{%1,%2},[%3];" ::"r"(dst), "f"(x), "f"(y), "r"(bar) : "memory");
}
__device__ __forceinline__ void sta1(uint32_t dst, uint32_t bar, uint32_t x) {
    asm volatile("st.async.weak.shared::cluster.mbarrier::complete_tx::bytes.b32 [%0],%1,[%2];" ::"r"(dst), "r"(x), "r"(bar) : "memory");
}
__device__ __forceinline__ void mbar_init(uint32_t bar, int cnt) { asm volatile("mbarrier.init.shared::cta.b64 [%0],%1;" ::"r"(bar), "r"(cnt) : "memory"); }
__device__ __forceinline__ void mbar_expect(uint32_t bar, int bytes) { asm volatile("mbarrier.arrive.expect_tx.shared::cta.b64 _,[%0],%1;" ::"r"(bar), "r"(bytes) : "memory"); }
__device__ __forceinline__ void mbar_wait(uint32_t bar, uint32_t parity) {
    uint32_t ok; int it = 0;
    while (true) {
        asm volatile("{.reg .pred p; mbarrier.try_wait.parity.relaxed.cluster.shared::cta.b64 p,[%1],%2; selp.u32 %0,1,0,p;}" : "=r"(ok) : "r"(bar), "r"(parity) : "memory");
        if (ok) break;
        if (++it > (1 << 20)) __trap();
    }
    asm volatile("fence.acquire.sync_restrict::shared::cluster.cluster;" ::: "memory");
}
__device__ __forceinline__ uint32_t mbar_try(uint32_t bar) {
    uint32_t ok; asm volatile("{.reg .pred p; mbarrier.try_wait.parity.relaxed.cluster.shared::cta.b64 p,[%1],0; selp.u32 %0,1,0,p;}" : "=r"(ok) : "r"(bar) : "memory"); return ok;
}
__device__ __forceinline__ void acq_fence() { asm volatile("fence.acquire.sync_restrict::shared::cluster.cluster;" ::: "memory"); }
__device__ __forceinline__ void mbar_wait_nf(uint32_t bar) {
    uint32_t ok; int it = 0;
    while (true) {
        asm volatile("{.reg .pred p; mbarrier.try_wait.parity.shared::cta.b64 p,[%1],0; selp.u32 %0,1,0,p;}" : "=r"(ok) : "r"(bar) : "memory");
        if (ok) break;
        if (++it > (1 << 20)) __trap();
    }
}
__device__ __forceinline__ bool elect() {
    uint32_t p; asm volatile("{.reg .pred p; elect.sync _|p,0xffffffff; selp.u32 %0,1,0,p;}" : "=r"(p)); return p;
}
__device__ __forceinline__ void tma3d(uint32_t dst, const CUtensorMap* map, int x, int y, int z, uint32_t bar) {
    asm volatile("cp.async.bulk.tensor.3d.shared::cluster.global.mbarrier::complete_tx::bytes [%0],[%1,{%2,%3,%4}],[%5];" ::"r"(dst), "l"(map), "r"(x), "r"(y), "r"(z), "r"(bar) : "memory");
}
#define EVF 0
__device__ __forceinline__ void tma4d(uint32_t dst, const CUtensorMap* map, int z, int w, uint32_t bar) {
    asm volatile("cp.async.bulk.tensor.4d.shared::cluster.global.mbarrier::complete_tx::bytes.L2::cache_hint [%0],[%1,{%2,%2,%3,%4}],[%5],%6;"
                 ::"r"(dst), "l"(map), "r"(0), "r"(z), "r"(w), "r"(bar), "l"(EVF ? 0x12F0000000000000ull : 0x1000000000000000ull) : "memory");
}
__device__ __forceinline__ void bulk_g2s(uint32_t dst, const void* src, int bytes, uint32_t bar) {
    asm volatile("cp.async.bulk.shared::cluster.global.mbarrier::complete_tx::bytes [%0],[%1],%2,[%3];" ::"r"(dst), "l"(src), "r"(bytes), "r"(bar) : "memory");
}
__device__ __forceinline__ void tma2d(uint32_t dst, const CUtensorMap* map, int x, int y, uint32_t bar) {
    asm volatile("cp.async.bulk.tensor.2d.shared::cluster.global.mbarrier::complete_tx::bytes [%0],[%1,{%2,%3}],[%4];" ::"r"(dst), "l"(map), "r"(x), "r"(y), "r"(bar) : "memory");
}
__device__ __forceinline__ void tma_red2d(const CUtensorMap* map, int x, int y, uint32_t src) {
    asm volatile("cp.reduce.async.bulk.tensor.3d.global.shared::cta.add.tile.bulk_group [%0,{%1,%2,%3}],[%4];" ::"l"(map), "r"(0), "r"(y), "r"(x), "r"(src) : "memory");
    asm volatile("cp.async.bulk.commit_group;" ::: "memory");
}
template <int ID, int N> __device__ __forceinline__ void bar_sync() { asm volatile("bar.sync %0,%1;" ::"n"(ID), "n"(N) : "memory"); }
template <int ID, int N> __device__ __forceinline__ void bar_arrive() { asm volatile("bar.arrive %0,%1;" ::"n"(ID), "n"(N) : "memory"); }
__device__ __forceinline__ uint4 ld_poll(const void* p) {
    uint4 v; asm volatile("ld.relaxed.gpu.global.v4.u32 {%0,%1,%2,%3},[%4];" : "=r"(v.x), "=r"(v.y), "=r"(v.z), "=r"(v.w) : "l"(p) : "memory"); return v;
}
__device__ __forceinline__ bool poll_bad(const uint4& a, const uint4& b, const uint4& c, const uint4& d) {
    return __any_sync(0xffffffffu, (a.w & b.w & c.w & d.w & 0x40000000u) == 0);
}
__device__ __forceinline__ void red_bf16x8(void* p, uint32_t x, uint32_t y, uint32_t z, uint32_t w) {
    asm volatile("red.relaxed.gpu.global.add.noftz.v4.bf16x2 [%0],{%1,%2,%3,%4};" ::"l"(p), "r"(x), "r"(y), "r"(z), "r"(w) : "memory");
}
__device__ __forceinline__ float ex2(float x) { float y; asm("ex2.approx.ftz.f32 %0,%1;" : "=f"(y) : "f"(x)); return y; }
__device__ __forceinline__ float rcp(float x) { float y; asm("rcp.approx.ftz.f32 %0,%1;" : "=f"(y) : "f"(x)); return y; }
__device__ __forceinline__ uint32_t clk() { uint64_t c; asm volatile("mov.u64 %0,%%clock64;" : "=l"(c)::"memory"); return (uint32_t)c; }
__device__ __forceinline__ uint32_t hadd(uint32_t a, uint32_t b) { uint32_t r; asm("add.rn.bf16x2 %0,%1,%2;" : "=r"(r) : "r"(a), "r"(b)); return r; }
__device__ __forceinline__ void cluster_sync() { asm volatile("barrier.cluster.arrive.release.aligned; barrier.cluster.wait.acquire.aligned;" ::: "memory"); }
__device__ __forceinline__ float4 sum4(float4 a, float4 b, float4 c, float4 d) {
    return make_float4((a.x + b.x) + (c.x + d.x), (a.y + b.y) + (c.y + d.y), (a.z + b.z) + (c.z + d.z), (a.w + b.w) + (c.w + d.w));
}
#define FENCE() asm volatile("griddepcontrol.launch_dependents;" ::: "memory")
template <int TB> __device__ __forceinline__ void wgmma32(float* d, const uint4& a, uint64_t desc, bool accumulate) {
    if (accumulate) asm volatile("{.reg .pred p; setp.ne.b32 p,1,0;\n"
                 "wgmma.mma_async.sync.aligned.m64n32k16.f32.bf16.bf16 {%0,%1,%2,%3,%4,%5,%6,%7,%8,%9,%10,%11,%12,%13,%14,%15},{%16,%17,%18,%19},%20,p,1,1,%21;}"
                 : "+f"(d[0]), "+f"(d[1]), "+f"(d[2]), "+f"(d[3]), "+f"(d[4]), "+f"(d[5]), "+f"(d[6]), "+f"(d[7]), "+f"(d[8]), "+f"(d[9]), "+f"(d[10]), "+f"(d[11]), "+f"(d[12]), "+f"(d[13]), "+f"(d[14]), "+f"(d[15])
                 : "r"(a.x), "r"(a.y), "r"(a.z), "r"(a.w), "l"(desc), "n"(TB));
    else asm volatile("{.reg .pred p; setp.ne.b32 p,0,0;\n"
                 "wgmma.mma_async.sync.aligned.m64n32k16.f32.bf16.bf16 {%0,%1,%2,%3,%4,%5,%6,%7,%8,%9,%10,%11,%12,%13,%14,%15},{%16,%17,%18,%19},%20,p,1,1,%21;}"
                 : "=f"(d[0]), "=f"(d[1]), "=f"(d[2]), "=f"(d[3]), "=f"(d[4]), "=f"(d[5]), "=f"(d[6]), "=f"(d[7]), "=f"(d[8]), "=f"(d[9]), "=f"(d[10]), "=f"(d[11]), "=f"(d[12]), "=f"(d[13]), "=f"(d[14]), "=f"(d[15])
                 : "r"(a.x), "r"(a.y), "r"(a.z), "r"(a.w), "l"(desc), "n"(TB));
}
template <int TB> __device__ __forceinline__ void wgmma224(float* d, const uint4& a, uint64_t desc, bool accumulate) {
    if (accumulate) asm volatile("{.reg .pred p; setp.ne.b32 p,1,0;\n"
                 "wgmma.mma_async.sync.aligned.m64n224k16.f32.bf16.bf16 {%0,%1,%2,%3,%4,%5,%6,%7,%8,%9,%10,%11,%12,%13,%14,%15,%16,%17,%18,%19,%20,%21,%22,%23,%24,%25,%26,%27,%28,%29,%30,%31,%32,%33,%34,%35,%36,%37,%38,%39,%40,%41,%42,%43,%44,%45,%46,%47,%48,%49,%50,%51,%52,%53,%54,%55,%56,%57,%58,%59,%60,%61,%62,%63,%64,%65,%66,%67,%68,%69,%70,%71,%72,%73,%74,%75,%76,%77,%78,%79,%80,%81,%82,%83,%84,%85,%86,%87,%88,%89,%90,%91,%92,%93,%94,%95,%96,%97,%98,%99,%100,%101,%102,%103,%104,%105,%106,%107,%108,%109,%110,%111},{%112,%113,%114,%115},%116,p,1,1,%117;}"
                 : "+f"(d[0]), "+f"(d[1]), "+f"(d[2]), "+f"(d[3]), "+f"(d[4]), "+f"(d[5]), "+f"(d[6]), "+f"(d[7]), "+f"(d[8]), "+f"(d[9]), "+f"(d[10]), "+f"(d[11]), "+f"(d[12]), "+f"(d[13]), "+f"(d[14]), "+f"(d[15]), "+f"(d[16]), "+f"(d[17]), "+f"(d[18]), "+f"(d[19]), "+f"(d[20]), "+f"(d[21]), "+f"(d[22]), "+f"(d[23]), "+f"(d[24]), "+f"(d[25]), "+f"(d[26]), "+f"(d[27]), "+f"(d[28]), "+f"(d[29]), "+f"(d[30]), "+f"(d[31]), "+f"(d[32]), "+f"(d[33]), "+f"(d[34]), "+f"(d[35]), "+f"(d[36]), "+f"(d[37]), "+f"(d[38]), "+f"(d[39]), "+f"(d[40]), "+f"(d[41]), "+f"(d[42]), "+f"(d[43]), "+f"(d[44]), "+f"(d[45]), "+f"(d[46]), "+f"(d[47]), "+f"(d[48]), "+f"(d[49]), "+f"(d[50]), "+f"(d[51]), "+f"(d[52]), "+f"(d[53]), "+f"(d[54]), "+f"(d[55]), "+f"(d[56]), "+f"(d[57]), "+f"(d[58]), "+f"(d[59]), "+f"(d[60]), "+f"(d[61]), "+f"(d[62]), "+f"(d[63]), "+f"(d[64]), "+f"(d[65]), "+f"(d[66]), "+f"(d[67]), "+f"(d[68]), "+f"(d[69]), "+f"(d[70]), "+f"(d[71]), "+f"(d[72]), "+f"(d[73]), "+f"(d[74]), "+f"(d[75]), "+f"(d[76]), "+f"(d[77]), "+f"(d[78]), "+f"(d[79]), "+f"(d[80]), "+f"(d[81]), "+f"(d[82]), "+f"(d[83]), "+f"(d[84]), "+f"(d[85]), "+f"(d[86]), "+f"(d[87]), "+f"(d[88]), "+f"(d[89]), "+f"(d[90]), "+f"(d[91]), "+f"(d[92]), "+f"(d[93]), "+f"(d[94]), "+f"(d[95]), "+f"(d[96]), "+f"(d[97]), "+f"(d[98]), "+f"(d[99]), "+f"(d[100]), "+f"(d[101]), "+f"(d[102]), "+f"(d[103]), "+f"(d[104]), "+f"(d[105]), "+f"(d[106]), "+f"(d[107]), "+f"(d[108]), "+f"(d[109]), "+f"(d[110]), "+f"(d[111])
                 : "r"(a.x), "r"(a.y), "r"(a.z), "r"(a.w), "l"(desc), "n"(TB));
    else asm volatile("{.reg .pred p; setp.ne.b32 p,0,0;\n"
                 "wgmma.mma_async.sync.aligned.m64n224k16.f32.bf16.bf16 {%0,%1,%2,%3,%4,%5,%6,%7,%8,%9,%10,%11,%12,%13,%14,%15,%16,%17,%18,%19,%20,%21,%22,%23,%24,%25,%26,%27,%28,%29,%30,%31,%32,%33,%34,%35,%36,%37,%38,%39,%40,%41,%42,%43,%44,%45,%46,%47,%48,%49,%50,%51,%52,%53,%54,%55,%56,%57,%58,%59,%60,%61,%62,%63,%64,%65,%66,%67,%68,%69,%70,%71,%72,%73,%74,%75,%76,%77,%78,%79,%80,%81,%82,%83,%84,%85,%86,%87,%88,%89,%90,%91,%92,%93,%94,%95,%96,%97,%98,%99,%100,%101,%102,%103,%104,%105,%106,%107,%108,%109,%110,%111},{%112,%113,%114,%115},%116,p,1,1,%117;}"
                 : "=f"(d[0]), "=f"(d[1]), "=f"(d[2]), "=f"(d[3]), "=f"(d[4]), "=f"(d[5]), "=f"(d[6]), "=f"(d[7]), "=f"(d[8]), "=f"(d[9]), "=f"(d[10]), "=f"(d[11]), "=f"(d[12]), "=f"(d[13]), "=f"(d[14]), "=f"(d[15]), "=f"(d[16]), "=f"(d[17]), "=f"(d[18]), "=f"(d[19]), "=f"(d[20]), "=f"(d[21]), "=f"(d[22]), "=f"(d[23]), "=f"(d[24]), "=f"(d[25]), "=f"(d[26]), "=f"(d[27]), "=f"(d[28]), "=f"(d[29]), "=f"(d[30]), "=f"(d[31]), "=f"(d[32]), "=f"(d[33]), "=f"(d[34]), "=f"(d[35]), "=f"(d[36]), "=f"(d[37]), "=f"(d[38]), "=f"(d[39]), "=f"(d[40]), "=f"(d[41]), "=f"(d[42]), "=f"(d[43]), "=f"(d[44]), "=f"(d[45]), "=f"(d[46]), "=f"(d[47]), "=f"(d[48]), "=f"(d[49]), "=f"(d[50]), "=f"(d[51]), "=f"(d[52]), "=f"(d[53]), "=f"(d[54]), "=f"(d[55]), "=f"(d[56]), "=f"(d[57]), "=f"(d[58]), "=f"(d[59]), "=f"(d[60]), "=f"(d[61]), "=f"(d[62]), "=f"(d[63]), "=f"(d[64]), "=f"(d[65]), "=f"(d[66]), "=f"(d[67]), "=f"(d[68]), "=f"(d[69]), "=f"(d[70]), "=f"(d[71]), "=f"(d[72]), "=f"(d[73]), "=f"(d[74]), "=f"(d[75]), "=f"(d[76]), "=f"(d[77]), "=f"(d[78]), "=f"(d[79]), "=f"(d[80]), "=f"(d[81]), "=f"(d[82]), "=f"(d[83]), "=f"(d[84]), "=f"(d[85]), "=f"(d[86]), "=f"(d[87]), "=f"(d[88]), "=f"(d[89]), "=f"(d[90]), "=f"(d[91]), "=f"(d[92]), "=f"(d[93]), "=f"(d[94]), "=f"(d[95]), "=f"(d[96]), "=f"(d[97]), "=f"(d[98]), "=f"(d[99]), "=f"(d[100]), "=f"(d[101]), "=f"(d[102]), "=f"(d[103]), "=f"(d[104]), "=f"(d[105]), "=f"(d[106]), "=f"(d[107]), "=f"(d[108]), "=f"(d[109]), "=f"(d[110]), "=f"(d[111])
                 : "r"(a.x), "r"(a.y), "r"(a.z), "r"(a.w), "l"(desc), "n"(TB));
}
template <int TB> __device__ __forceinline__ void wgmma112(float* d, uint64_t da, uint64_t db, bool accumulate) {
    if (accumulate) asm volatile("{.reg .pred p; setp.ne.b32 p,1,0;\n"
                 "wgmma.mma_async.sync.aligned.m64n112k16.f32.bf16.bf16 {%0,%1,%2,%3,%4,%5,%6,%7,%8,%9,%10,%11,%12,%13,%14,%15,%16,%17,%18,%19,%20,%21,%22,%23,%24,%25,%26,%27,%28,%29,%30,%31,%32,%33,%34,%35,%36,%37,%38,%39,%40,%41,%42,%43,%44,%45,%46,%47,%48,%49,%50,%51,%52,%53,%54,%55},%56,%57,p,1,1,0,%58;}"
                 : "+f"(d[0]), "+f"(d[1]), "+f"(d[2]), "+f"(d[3]), "+f"(d[4]), "+f"(d[5]), "+f"(d[6]), "+f"(d[7]), "+f"(d[8]), "+f"(d[9]), "+f"(d[10]), "+f"(d[11]), "+f"(d[12]), "+f"(d[13]), "+f"(d[14]), "+f"(d[15]), "+f"(d[16]), "+f"(d[17]), "+f"(d[18]), "+f"(d[19]), "+f"(d[20]), "+f"(d[21]), "+f"(d[22]), "+f"(d[23]), "+f"(d[24]), "+f"(d[25]), "+f"(d[26]), "+f"(d[27]), "+f"(d[28]), "+f"(d[29]), "+f"(d[30]), "+f"(d[31]), "+f"(d[32]), "+f"(d[33]), "+f"(d[34]), "+f"(d[35]), "+f"(d[36]), "+f"(d[37]), "+f"(d[38]), "+f"(d[39]), "+f"(d[40]), "+f"(d[41]), "+f"(d[42]), "+f"(d[43]), "+f"(d[44]), "+f"(d[45]), "+f"(d[46]), "+f"(d[47]), "+f"(d[48]), "+f"(d[49]), "+f"(d[50]), "+f"(d[51]), "+f"(d[52]), "+f"(d[53]), "+f"(d[54]), "+f"(d[55])
                 : "l"(da), "l"(db), "n"(TB));
    else asm volatile("{.reg .pred p; setp.ne.b32 p,0,0;\n"
                 "wgmma.mma_async.sync.aligned.m64n112k16.f32.bf16.bf16 {%0,%1,%2,%3,%4,%5,%6,%7,%8,%9,%10,%11,%12,%13,%14,%15,%16,%17,%18,%19,%20,%21,%22,%23,%24,%25,%26,%27,%28,%29,%30,%31,%32,%33,%34,%35,%36,%37,%38,%39,%40,%41,%42,%43,%44,%45,%46,%47,%48,%49,%50,%51,%52,%53,%54,%55},%56,%57,p,1,1,0,%58;}"
                 : "=f"(d[0]), "=f"(d[1]), "=f"(d[2]), "=f"(d[3]), "=f"(d[4]), "=f"(d[5]), "=f"(d[6]), "=f"(d[7]), "=f"(d[8]), "=f"(d[9]), "=f"(d[10]), "=f"(d[11]), "=f"(d[12]), "=f"(d[13]), "=f"(d[14]), "=f"(d[15]), "=f"(d[16]), "=f"(d[17]), "=f"(d[18]), "=f"(d[19]), "=f"(d[20]), "=f"(d[21]), "=f"(d[22]), "=f"(d[23]), "=f"(d[24]), "=f"(d[25]), "=f"(d[26]), "=f"(d[27]), "=f"(d[28]), "=f"(d[29]), "=f"(d[30]), "=f"(d[31]), "=f"(d[32]), "=f"(d[33]), "=f"(d[34]), "=f"(d[35]), "=f"(d[36]), "=f"(d[37]), "=f"(d[38]), "=f"(d[39]), "=f"(d[40]), "=f"(d[41]), "=f"(d[42]), "=f"(d[43]), "=f"(d[44]), "=f"(d[45]), "=f"(d[46]), "=f"(d[47]), "=f"(d[48]), "=f"(d[49]), "=f"(d[50]), "=f"(d[51]), "=f"(d[52]), "=f"(d[53]), "=f"(d[54]), "=f"(d[55])
                 : "l"(da), "l"(db), "n"(TB));
}
__device__ __forceinline__ uint64_t mdesc(uint32_t addr, uint32_t lbo, uint32_t sbo, int swz) {
    return (uint64_t)((addr & 0x3FFFF) >> 4) | ((uint64_t)(lbo >> 4) << 16) | ((uint64_t)(sbo >> 4) << 32) | ((uint64_t)swz << 62);
}
template <int N> __device__ __forceinline__ void wg_wait() { asm volatile("wgmma.wait_group.sync.aligned %0;" ::"n"(N) : "memory"); }
__device__ __forceinline__ void bar_sync(int id, int n) { asm volatile("bar.sync %0,%1;" ::"r"(id), "r"(n) : "memory"); }
__device__ __forceinline__ void bar_arrive(int id, int n) { asm volatile("bar.arrive %0,%1;" ::"r"(id), "r"(n) : "memory"); }
__device__ __forceinline__ int ld_flag(const int* p) { int v; asm volatile("ld.relaxed.gpu.global.s32 %0,[%1];" : "=r"(v) : "l"(p) : "memory"); return v; }
__device__ __forceinline__ void st_flag(int* p, int v) { asm volatile("st.relaxed.gpu.global.s32 [%0],%1;" ::"l"(p), "r"(v) : "memory"); }
__device__ __forceinline__ void fence_gpu() { asm volatile("fence.acq_rel.gpu;" ::: "memory"); }
__device__ __forceinline__ void wait_flag(const int* p, int need) {
    int it = 0;
    while (__any_sync(0xffffffffu, ld_flag(p) < need)) { if (++it > (1 << 20)) __trap(); }
}
__device__ __forceinline__ void retire(int total) {
    int n = 0;
    if (elect()) n = atomicAdd(&g_FLAG[F_DONE * 32], 1);
    if (__any_sync(0xffffffffu, n == total - 1)) {
#pragma unroll 1
        for (int i = threadIdx.x & 31; i < 2 * 197; i += 32) ((uint4*)g_FLAG)[(i >> 1) * 8 + (i & 1)] = make_uint4(0, 0, 0, 0);
        __syncwarp();
    }
}
__device__ __forceinline__ void sts32(uint32_t a, uint32_t x) { asm volatile("st.shared.u32 [%0],%1;" ::"r"(a), "r"(x) : "memory"); }
__device__ __forceinline__ uint32_t packv(float lo, float hi) { uint32_t r; asm volatile("cvt.rn.bf16x2.f32 %0,%1,%2;" : "=r"(r) : "f"(hi), "f"(lo)); return r; }
constexpr float LOG2E = 1.4426950408889634f;

struct Maps { CUtensorMap x, out, acc, k64, v64, q224, o224, rk, rv, u8, o8; };
__device__ __forceinline__ uint4 ldcg(const uint4* p) {
    uint4 v; asm volatile("ld.global.cg.v4.u32 {%0,%1,%2,%3},[%4];" : "=r"(v.x), "=r"(v.y), "=r"(v.z), "=r"(v.w) : "l"(p) : "memory"); return v;
}
__device__ __forceinline__ void red_flag(int* p) { asm volatile("red.relaxed.gpu.global.add.s32 [%0],1;" ::"l"(p) : "memory"); }

#define QFULL 0
#define HOLD 0
#define STAGED 1
template <class Side>
__device__ __forceinline__ void fold(uint32_t so, uint32_t sa, int sd, uint32_t bs, uint32_t bar, int n, int ntile, uint32_t order, const Maps& maps, Side side) {
    const int tid = threadIdx.x, lane = tid & 31, wid = __shfl_sync(0xffffffffu, tid >> 5, 0), wg = wid >> 2, u = wid & 3;
    const int g = lane >> 2, t = lane & 3, M = n >> 5, h = (n >> 1) & 15, hf = n & 1;
    auto stream = [&](int i) { tma4d(sa + (i % 3) * sd, M ? &maps.v64 : &maps.k64, 4 * h, 8 * ((order >> (4 * i)) & 7), bar + 16 + i * 8); };
    auto resident = [&](int e) {
        tma4d(bs + e * 57344, M ? &maps.o224 : &maps.q224, M ? 7 * hf : 4 * h + 2 * e, M ? h * 32 + 16 * e : 28 * hf, bar + e * 8);
    };
    if (wid == 7) {
        if (elect()) {
#pragma unroll
            for (int i = 0; i < 7; i++) mbar_init(bar + i * 8, 1);
            asm volatile("fence.mbarrier_init.release.cluster;" ::: "memory");
#pragma unroll
            for (int i = 0; i < 6; i++) mbar_expect(bar + i * 8, i < 2 ? 57344 : 32768);
            if (ntile == 3) { const uint32_t t0 = clk(); while ((int)(clk() - t0) < HOLD) {} }
            GE(ntile - 3, 10); stream(0); GE(ntile - 3, 11);
        }
        __syncwarp();
    }
    bar_sync<15, 256>();
    if (wid == 7) {
        if (elect()) {
            if (STAGED == 2) mbar_wait_nf(bar + 16);
            resident(0); GE(ntile - 3, 12);
            if (STAGED) mbar_wait_nf(STAGED == 2 ? bar : bar + 16);
            resident(1); GE(ntile - 3, 13);
            if (STAGED) mbar_wait_nf(STAGED == 2 ? bar + 8 : bar);
            stream(1); GE(ntile - 3, 14);
            if (STAGED == 1) mbar_wait_nf(bar + 8);
            stream(2); GE(ntile - 3, 15);
        }
        __syncwarp();
    } else if (wg == 1) side();
    const float sc = M ? 1.f : LOG2E / 16.f;
    uint4 a[16];
    auto fetch = [&](int i) {
        mbar_wait_nf(bar + 16 + i * 8);
        const uint32_t r = sa + (i % 3) * sd + u * 8192 + (lane & 8) * 512 + (lane & 7) * 128;
#pragma unroll
        for (int k = 0; k < 16; k++) a[k] = ldsm4(r + (k >> 2) * 1024 + (((2 * (k & 3) + (lane >> 4)) ^ (lane & 7)) << 4));
    };
    fetch(wg);
#pragma unroll 1
    for (int i = wg; i < ntile; i += 2) {
        float d[112];
        const uint64_t db = M == 0 ? mdesc(bs + (i >> 8), 16, QFULL ? 4096 : 2048, 1) : mdesc(bs + (i >> 8), 512, 3584, 2);
        GF(ntile - 3, 4 + (i >> 1));
        if (i > 0) bar_sync(13 + wg, 256);
        if (i == 1) {
            if (ntile == 4 && wid == 7) { if (elect()) stream(3); __syncwarp(); }
            bar_arrive<12, 256>();
        }
#pragma unroll
        for (int e = 0; e < 2; e++) {
            mbar_wait_nf(bar + e * 8);
            if (QFULL && M == 0) mbar_wait_nf(bar + 8);
            if (i < 2) GF(ntile - 3, e);
            if (M == 0) {
                wg_fence();
#pragma unroll
                for (int k = 0; k < 8; k++) wgmma224<0>(d, a[8 * e + k], db + ((e * (QFULL ? 2048 : 57344) + (k >> 2) * 1024 + (k & 3) * 32) >> 4), 8 * e + k);
                wg_commit();
            } else {
                wg_fence();
#pragma unroll
                for (int k = 0; k < 8; k++) wgmma224<1>(d, a[8 * e + k], db + ((e * 57344 + k * 7168) >> 4), 8 * e + k);
                wg_commit();
            }
        }
        if (i + 1 < ntile) bar_arrive(14 - wg, 256);
        if (i >= 2 && !(u & 1)) {
            if (elect()) { asm volatile("cp.async.bulk.wait_group 0;" ::: "memory"); red_flag(g_FLAG + (F_IMG + n) * 32 + ((order >> (4 * wg)) & 7)); }
            __syncwarp();
        }
        if (ntile == 4 && i >= 2) wait_flag(&g_FLAG[F_XA * 32], 192);
        wg_wait<0>();
        if (i == 3) bar_arrive<9, 160>();
        GF(ntile - 3, 8 + (i >> 1));
        if (i + 2 < ntile) fetch(i + 2);
        if (i == 0) { bar_sync<12, 256>(); bar_arrive<11, 256>(); }
        if (i == 1) bar_sync<11, 256>();
        if (ntile == 4) { if (i == 1) bar_arrive<10, 256>(); if (i == 2) bar_sync<10, 256>(); }
        const int tile = (order >> (4 * i)) & 7;
        const uint32_t o = so + tile * 28672 + (u >> 1) * 14336, fa = o + (g >> 1) * 3584 + (u & 1) * 256 + (g & 1) * 64;
#pragma unroll
        for (int j = 0; j < 14; j++) {
            const float* e = d + 16 * (j >> 1) + 2 * (j & 1);
            sts128(fa + (j & 1) * 128 + (j >> 1) * 512 + ((t ^ (2 * (u & 1) + (j & 1))) << 4),
                   pack(e[0] * sc, e[1] * sc), pack(e[4] * sc, e[5] * sc), pack(e[8] * sc, e[9] * sc), pack(e[12] * sc, e[13] * sc));
        }
        asm volatile("fence.proxy.async.shared::cta;" ::: "memory");
        bar_sync(4 + (wid >> 1), 64);
        if (!(u & 1)) {
            if (elect()) asm volatile("cp.async.bulk.global.shared::cta.bulk_group [%0],[%1],14336; cp.async.bulk.commit_group;"
                                      ::"l"(g_FI + (size_t)n * 200704 + tile * 28672 + (u >> 1) * 14336), "r"(o) : "memory");
            __syncwarp();
        }
    }
}
__device__ __forceinline__ void fold_done(int n, int tile) {
    if (!(__shfl_sync(0xffffffffu, threadIdx.x, 0) & 32)) {
        if (elect()) { asm volatile("cp.async.bulk.wait_group 0;" ::: "memory"); red_flag(g_FLAG + (F_IMG + n) * 32 + tile); }
        __syncwarp();
    }
}

#define OWIDE 1
#define POLL_DELAY 465
#define DBGW 1
#define TMA_DELAY 50
constexpr int NST = 5;
constexpr int S_KQ = 0, S_V = 7168, S_XX = 14336, STGB = RECC, XB = 7168;
constexpr int R_BK = 31744;
constexpr int R_STG = R_BK + 3 * 8192;
constexpr int R_ST2 = R_STG + NST * STGB;
constexpr int R_OUT = R_ST2 + 2 * XB;
constexpr int R_W0 = 0;
constexpr int R_MB = R_OUT + 2 * 7168;
constexpr int R_SXJ = R_MB + 4 * 3584;
constexpr int R_SMI = R_SXJ + 1024;
constexpr int R_SMX = R_SMI + 2048;
constexpr int R_SMM = R_SMX + 1024;
constexpr int R_SME = R_SMM + 1024;
constexpr int R_UP = R_SME + 512;
constexpr int R_UB = R_UP + 8192;
constexpr int R_SXI = R_UB + 8192;
constexpr int R_LX = R_SXI + 4096;
constexpr int R_PB = R_LX + 2 * 1024;
constexpr int R_BAR = R_PB + 4 * 2176;
constexpr int B_KV = 0, B_SX = 512, B_SM = 1024, B_L1 = 1536, B_L2 = 2048, B_BK = 2560, B_F = 3072;
constexpr int R_SMEM = R_BAR + 3200;
constexpr int F_B = 98304;
static_assert(F_B + 114688 <= R_BAR, "folding buffers");
static_assert(R_SMEM <= 232448, "smem");
constexpr uint32_t ONE2 = 0x3f803f80u, CNT16 = 0x40000000u, CNT1 = 0x3e003e00u;
enum { BR = 1, BX, BG, BS, BU, BL, BO, BV, BH };

#define DBG(i)

__device__ __forceinline__ void load_stage(uint32_t sb, int seg, uint32_t stg, int h, int c, const CUtensorMap* mapX) {
    const uint32_t bar = sb + R_BAR + B_KV + seg * 8, dst = sb + R_STG + stg;
    const int r = ((seg % RING) * 16 + h) * 4;
    bulk_g2s(dst, g_REC + (size_t)(r + c) * RECC, RECC, bar);
    tma3d(sb + R_ST2 + (seg & 1) * XB, mapX, 0, 32 * seg, 7 * c, bar);
}

template <int V> struct Int { static constexpr int value = V; };
__host__ __device__ constexpr int KS(int j) { return (j & 1) ? j >> 1 : 3 + (j >> 1); }

__global__ void __cluster_dims__(CLUSTER, 1, 1) __launch_bounds__(256, 1)
k_rec(const __nv_bfloat16* __restrict__ mem0, const __nv_bfloat16* __restrict__ x, __nv_bfloat16* __restrict__ out, const __grid_constant__ Maps maps, int total) {
    extern __shared__ __align__(1024) uint8_t smem[];
    const uint32_t sb = smem_u32(smem);
    const int tid = threadIdx.x, wid = __shfl_sync(0xffffffffu, tid >> 5, 0), w = wid & 3;
    const int lane = __shfl_sync(0xffffffffu, tid & 31, tid & 31);
    const int g = lane >> 2, t = lane & 3;
    const int h = blockIdx.x >> 2, c = blockIdx.x & 3;

    FENCE();
    if (tid == 0) GT(0, 0);
    if (sb != 1024 + (sb & 0xff000000u)) __trap();
    asm volatile("prefetch.tensormap [%0];" ::"l"(&maps.x + wid) : "memory");
    const int M = wid >> 2;
    {
        const int n = (c >> 1) * 32 + 2 * h + (c & 1);
        uint4 l[10], q[10];
        if (M == 1 && w < 3) {
#pragma unroll
            for (int i = 0; i < 10; i++) {
                const uint4* p = (const uint4*)(x + (size_t)(32 * blockIdx.x + 16 * (i & 1) + g) * D) + 4 * min(w + 3 * (i >> 1), 13) + t;
                l[i] = __ldg(p); q[i] = __ldg(p + 8 * 56);
            }
        }
        if (tid < 112) asm volatile("prefetch.global.L2 [%0];" ::"l"(mem0 + tid * 32) : "memory");
        auto side = [&]() {
#pragma unroll
            for (int i = 0; i < 10; i++) {
                uint4* o = g_XA + (2 * blockIdx.x + (i & 1)) * 896 + 64 * min(w + 3 * (i >> 1), 13) + lane;
                o[0] = make_uint4(l[i].x, q[i].x, l[i].y, q[i].y); o[32] = make_uint4(l[i].z, q[i].z, l[i].w, q[i].w);
            }
            {
                uint4* z = w == 2 ? (uint4*)g_ACC + blockIdx.x * 64 : (uint4*)(out + (size_t)(2 * blockIdx.x + w) * OUTW + D);
                z[lane] = make_uint4(0, 0, 0, 0);
                if (w == 2 || lane < 24) z[32 + lane] = make_uint4(0, 0, 0, 0);
            }
            __syncwarp();
            if (elect()) asm volatile("red.release.gpu.global.add.s32 [%0],1;" ::"l"(&g_FLAG[F_XA * 32]) : "memory");
            __syncwarp();
        };
        const uint32_t order = (c & 1) ? 0x645 : 0x021;
        fold(sb - (c & 1) * 114688, sb, 32768, sb + F_B, sb + R_BAR + B_F, n, 3, order, maps, side);
        fold_done(n, (order >> (M ? 4 : 8)) & 7);
        if (M == 1) {
            if (elect()) {
#pragma unroll 32
                for (int i = 0; i < 96; i++) mbar_init(sb + R_BAR + w * 768 + i * 8, 1);
                asm volatile("fence.mbarrier_init.release.cluster;" ::: "memory");
            }
            __syncwarp();
#pragma unroll
            for (int i = 0; i < 3; i++) {
                const int kind = (3 * w + i) >> 1;
                mbar_expect(sb + R_BAR + w * 768 + i * 256 + lane * 8, kind == 0 ? STGB + XB : (kind == 1 ? 512 : (kind == 2 ? 768 + 1024 : (kind == 3 ? 1024 : (kind == 4 ? 2176 : 8192)))));
            }
        }
    }
    if (tid == 0) GT(0, 5);
    auto opq = [&](uint32_t x) { return __shfl_sync(0xffffffffu, x, lane); };
    const uint32_t lw = opq(sb + lane * 16 + w * 3584);
    uint4 wr[7][6];
    {
        const int n = M * 32 + 2 * h + (c >> 1);
        bar_sync<15, 256>();
        asm volatile("barrier.cluster.arrive.relaxed.aligned;" ::: "memory");
        wait_flag(g_FLAG + (F_IMG + n) * 32 + min(((7 * w) >> 2) + lane, (7 * w + 6) >> 2), 2);
        if (tid == 0) GT(0, 6);
        const uint8_t* img = g_FI + (size_t)n * 200704 + (g >> 1) * 3584 + (g & 1) * 64 + (c & 1) * 1536;
        uint4 z[7][2][4];
        auto request = [&](int j) {
#pragma unroll
            for (int hi = 0; hi < 2; hi++) {
                const int k8 = 14 * w + 2 * KS(j) + hi;
                const uint4* p = (const uint4*)(img + (k8 >> 2) * 14336 + (k8 & 3) * 128 + ((t ^ (k8 & 3)) << 4));
#pragma unroll
                for (int q = 0; q < 4; q++) z[j][hi][q] = ldcg(p + q * 32);
            }
        };
        auto fetch = [&](auto odd) {
            request(0); request(1); request(2); request(3);
#pragma unroll
            for (int j = 0; j < 7; j++) {
                FENCE();
#pragma unroll
                for (int m = 0; m < 7; m++) {
                    const int i = m + odd.value;
                    const uint4 &lo = z[j][0][i >> 1], &hi = z[j][1][i >> 1];
                    const uint4 a = (i & 1) ? make_uint4(movm(lo.z), movm(lo.w), movm(hi.z), movm(hi.w)) : make_uint4(movm(lo.x), movm(lo.y), movm(hi.x), movm(hi.y));
                    if (j == 0) sts128(lw + R_W0 + M * 14336 + m * 512, a); else wr[m][j - 1] = a;
                }
                FENCE();
                if (j < 3) request(j + 4);
            }
        };
        if (c & 1) fetch(Int<1>()); else fetch(Int<0>());
    }
    if (tid == 0) GT(0, 1);
    asm volatile("barrier.cluster.wait.aligned;" ::: "memory");
    const uint32_t l16 = opq(sb + lane * 16), l8 = opq(sb + lane * 8);
    const uint32_t lp = opq(sb + (lane & 7) * 16 + ((lane >> 4) + ((lane >> 2) & 2)) * 128);
    const uint32_t rsb = mapa(sb, (c + w) & 3);
    const int tl0 = 6 + 2 * w, tl2 = w == 3 ? 3 : 2 * w, tl3 = w < 2 ? 1 : 5;

    if (wid < 4) {
        const int poff = (w * 4 + (lane >> 3)) * 256 + (lane & 7) * 16;
        const uint8_t* pp = g_ACC + poff;
        uint4 v0, v1, v2, v3;
        {
            const uint32_t* p = (const uint32_t*)(mem0 + g * D + 112 * w + 2 * t);
            const uint32_t a = p[4], b = p[20];
            v0 = make_uint4(p[24], p[28], p[0], (a & 0xffffu) | CNT16); v1 = make_uint4(p[32], p[36], p[8], (a >> 16) | CNT16);
            v2 = make_uint4(p[40], p[44], p[16], (b & 0xffffu) | CNT16); v3 = make_uint4(p[48], p[52], p[12], (b >> 16) | CNT16);
        }
        const int rdelta = ((0x2130 >> (4 * w)) & 3) * 4096 + (c - w) * 1024;
        const uint32_t rdst = opq(rsb + R_SMM + ((4 - w) & 3) * 256 + lane * 8);
        uint32_t rbar = opq(rsb + R_BAR + B_SM + (lw & 15));
        const uint32_t psel = (w & 1) ? 0x7632u : 0x7610u;
        const uint32_t mb = lw + R_MB, ac = opq(l16 + R_MB + c * 3584), a8w = opq(l8 + w * 256);
        uint32_t vaA = opq(sb + R_STG + S_V + (lane & 15) * 16 + (tl0 + (lane >> 4)) * 512), vaB = opq(sb + R_STG + S_V + (lane & 15) * 16 + (lane < 16 ? tl2 : tl3) * 512);
        uint32_t kq = opq(lp + R_STG + S_KQ + w * 1792);
        const uint32_t smt = opq(sb + R_SMI + w * 256 + t * 64 + g * 4);
        uint32_t roff = opq(poff + rdelta + 128);
        const uint32_t rdump = 4 * 16384;
        const uint32_t uba = opq(sb + R_UB + (lane < 16 ? tl0 + (lane >> 3) : (lane < 24 ? tl2 : tl3)) * 128 + (lane & 7) * 16);
        uint32_t stg = 0;
        mbar_wait_nf(sb + R_BAR + B_KV);
        acq_fence();
        if (tid == 0) GT(0, 2);
#pragma unroll 1
        for (int s = 0; s < NSEG; s++) {
            const uint32_t bar = sb + R_BAR + s * 8;
            const uint4 k0 = ldsm4(kq), k1 = ldsm4(kq + 512), k2 = ldsm4(kq + 1024), k3 = ldsm4(kq + 1536);
            uint4 w0[7];
#pragma unroll
            for (int m = 0; m < 7; m++) if (m != 3 && m != 5) w0[m] = lds128v(lw + R_W0 + m * 512);
            DBG(12);
            FENCE();
            if (__builtin_expect(poll_bad(v0, v1, v2, v3), 0)) {
                int it = 0;
                uint32_t a = lw + (R_BK - w * 3072), an = a + 8192;
                do {
                    asm volatile("cp.async.commit_group;" ::: "memory");
                    asm volatile("cp.async.cg.shared.global [%0],[%1],16; cp.async.cg.shared.global [%0+6144],[%1+12288],16;"
                                 "cp.async.cg.shared.global [%0+2048],[%1+4096],16; cp.async.cg.shared.global [%0+4096],[%1+8192],16;" ::"r"(an), "l"(pp) : "memory");
                    if (it == 0) mbar_wait_nf(bar + B_BK); else asm volatile("cp.async.wait_group 0;" ::: "memory");
                    v0 = lds128(a); v1 = lds128(a + 6144); v2 = lds128(a + 2048); v3 = lds128(a + 4096);
                    a = an; an ^= 24576;
                    if (++it > (1 << 20)) __trap();
                } while (poll_bad(v0, v1, v2, v3));
            }
            const uint32_t b[14] = {v0.z | (lw & 15), __byte_perm(v0.w, v1.w, 0x5410), v1.z | (lw & 15), v3.z | (lw & 15), v2.z | (lw & 15), __byte_perm(v2.w, v3.w, 0x5410),
                                    v0.x, v0.y, v1.x, v1.y, v2.x, v2.y, v3.x, v3.y};
            float acc[7][4], sx[4], sy[4];
#define A(m, j) do { if ((j) == 0) mmaz(acc[m], w0[m], b[6], b[7]); else mma(acc[m], wr[m][(j) ? (j) - 1 : 0], b[2 * KS(j)], b[2 * KS(j) + 1]); } while (0)
#define ST(j) stsm2(mb + (j) * 256, b[2 * (j)], b[2 * (j) + 1])
#define TR(m) do { tb[2 * (m)] = movm(pack(acc[m][0], acc[m][1])); tb[2 * (m) + 1] = movm(pack(acc[m][2], acc[m][3])); } while (0)
            uint32_t tb[14];
            DBG(13);
            mmaz(sx, k3, b[12], b[13]); A(0, 0); FENCE();
            mmaz(sy, k2, b[10], b[11]); ST(6); A(1, 0); ST(5); FENCE();
            mma(sx, k2, b[8], b[9]); A(0, 1); ST(4); FENCE();
            mma(sy, k1, b[6], b[7]); A(1, 1); ST(3); FENCE();
            mma(sx, k1, b[4], b[5]); A(0, 2); ST(0); FENCE();
            mma(sy, k0, b[2], b[3]); A(1, 2); ST(2); FENCE();
            mma(sx, k0, b[0], b[1]); A(0, 3); ST(1); FENCE();
            A(6, 0); w0[3] = lds128(lw + R_W0 + 3 * 512); A(1, 3); FENCE();
            A(4, 0); w0[5] = lds128(lw + R_W0 + 5 * 512); A(0, 4); FENCE();
            A(6, 1); sts64f(a8w + R_SXJ, sx[0] + sy[2], sx[1] + sy[3]); A(1, 4);
            bar_sync<BX, 256>();
            acq_fence();
            A(4, 1); A(0, 5); A(6, 2); A(1, 5); FENCE();
            DBG(1);
            A(4, 2); A(0, 6); FENCE(); A(6, 3); A(1, 6); FENCE();
            A(2, 0); A(3, 0); FENCE(); A(6, 4); A(5, 0); FENCE();
            A(2, 1); TR(0); A(3, 1); FENCE(); A(6, 5); A(5, 1); FENCE();
            A(2, 2); TR(1); A(3, 2); FENCE(); A(6, 6); A(5, 2); const uint4 am0 = ldsm4(ac); FENCE();
            A(2, 3); A(3, 3); const uint2 am3 = ldsm2(ac + 1536); FENCE(); A(4, 3); A(5, 3); const uint4 am1 = ldsm4(ac + 512); FENCE();
            const uint32_t j0 = pack(acc[6][0], acc[6][1]), j1 = pack(acc[6][2], acc[6][3]);
            A(2, 4); tb[12] = movm(j0); A(3, 4); tb[13] = movm(j1); FENCE(); A(4, 4); A(5, 4); const uint4 am2 = ldsm4(ac + 1024); FENCE();
            A(2, 5); A(3, 5); FENCE(); A(4, 5); A(5, 5); FENCE();
            A(2, 6); A(3, 6); FENCE(); A(4, 6); A(5, 6); bar_arrive<BH, 256>(); FENCE();
            DBG(2);
            float sa[4], sc[4], se[4], sf[4];
            const uint4 tq0 = make_uint4(tb[0], tb[2], tb[1], tb[3]), tq3 = make_uint4(tb[12], j0, tb[13], j1);
            mmaz(sa, tq0, am0.x, am0.y); TR(2); FENCE(); mmaz(sc, tq0, am0.z, am0.w); TR(3); FENCE(); mmaz(se, tq3, am3.x, am3.y); TR(4); FENCE();
            TR(5); FENCE();
            const uint4 tq1 = make_uint4(tb[4], tb[6], tb[5], tb[7]), tq2 = make_uint4(tb[8], tb[10], tb[9], tb[11]);
            mma(sa, tq1, am1.x, am1.y); mma(sc, tq1, am1.z, am1.w); FENCE(); mma(se, tq2, am2.x, am2.y); mmaz(sf, tq2, am2.z, am2.w);
            bar_arrive<BG, 256>();
            FENCE();
            sts32f(smt, ((sa[0] + sc[2]) + se[0]) + sf[2]); sts32f(smt + 32, ((sa[1] + sc[3]) + se[1]) + sf[3]);
            DBG(3);
            bar_sync<BS, 128>();
            float s0, s1;
            {
                const float2 p0 = lds64f(l8 + R_SMI), p1 = lds64f(l8 + R_SMI + 256), p2 = lds64f(l8 + R_SMI + 512), p3 = lds64f(l8 + R_SMI + 768);
                s0 = ((p0.x + p1.x) + p2.x) + p3.x; s1 = ((p0.y + p1.y) + p2.y) + p3.y;
                if (w) sta2f(rdst, rbar, s0, s1);
            }
            DBG(4);
            const uint32_t one2a = ONE2 | (lw & 15), one2b = ONE2 | (lp & 15);
            float o[5][4];
            uint4 ub;
            uint2 h0, h1, h2, h3;
            uint32_t smok;
            {
                const uint32_t sxok = mbar_try(bar + B_SX);
                const uint4 va0 = ldsm4t(vaA), vc0 = ldsm4t(vaB), va1 = ldsm4t(vaA + 256), vc1 = ldsm4t(vaB + 256);
                FENCE();
                if (!sxok) mbar_wait(bar + B_SX, 0);
                const uint4 ea = ldsm4t(lp + R_SME), eb = ldsm4t(lp + R_SME + 256);
                bar_sync<BV, 256>();
                const uint2 e0 = lds64(a8w + R_UP), e1 = lds64(a8w + R_UP + 1024), e2 = lds64(a8w + R_UP + 2048), e3 = lds64(a8w + R_UP + 3072);
                FENCE();
                mmaz(o[4], ea, one2a, one2b); mmaz(o[0], ea, va0.x, va0.y); mmaz(o[1], ea, va0.z, va0.w); mmaz(o[2], ea, vc0.x, vc0.y); mmaz(o[3], ea, vc0.z, vc0.w);
                smok = mbar_try(bar + B_SM);
                FENCE();
                mma(o[4], eb, one2a, one2b); mma(o[0], eb, va1.x, va1.y); mma(o[1], eb, va1.z, va1.w); mma(o[2], eb, vc1.x, vc1.y); mma(o[3], eb, vc1.z, vc1.w);
                h0 = e0; h1 = e1; h2 = e2; h3 = e3;
            }
            DBG(5);
            FENCE();
            if (!smok) mbar_wait(bar + B_SM, 0);
            acq_fence();
            DBG(7);
            const float2 p1 = lds64f(l8 + R_SMM + 256), p2 = lds64f(l8 + R_SMM + 512), p3 = lds64f(l8 + R_SMM + 768);
            bar_sync<BU, 256>();
            const uint2 u0 = lds64(a8w + R_UP + 4096), u1 = lds64(a8w + R_UP + 5120), u2 = lds64(a8w + R_UP + 6144), u3 = lds64(a8w + R_UP + 7168);
            ub.z = hadd(hadd(h0.x, h1.x), hadd(h2.x, h3.x)); ub.w = hadd(hadd(h0.y, h1.y), hadd(h2.y, h3.y));
            ub.x = hadd(hadd(u0.x, u1.x), hadd(u2.x, u3.x)); ub.y = hadd(hadd(u0.y, u1.y), hadd(u2.y, u3.y));
            const float d0 = ((s0 + p1.x) + p2.x) + p3.x, d1 = ((s1 + p1.y) + p2.y) + p3.y;
            bool bad;
            {
                const float f0 = ex2(d0), f1 = ex2(d1);
                const uint32_t pm = pack(f0, f1), pj = pack(f1, f0);
                FENCE();
                mma8(o[4], pm, pj, one2a); mma8(o[3], pm, pj, ub.w); mma8(o[2], pm, pj, ub.z); mma8(o[0], pm, pj, ub.x); mma8(o[1], pm, pj, ub.y);
                const float r = rcp(o[4][0]);
                bad = __float_as_uint(o[4][0]) - 0x2f800000u > 0x20000000u;
                red_bf16x8(g_ACC + (bad ? rdump : roff), pack(o[0][0] * r, o[0][1] * r), pack(o[1][0] * r, o[1][1] * r), pack(o[2][0] * r, o[2][1] * r),
                           __byte_perm(pack(o[3][0] * r, o[3][1] * r), CNT1, psel));
            }
            FENCE();
            const uint32_t t0 = clk();
            DBG(8);
            float de[16], dx[16];
            const uint64_t desc = (uint64_t)(((sb + R_ST2 + (s & 1) * XB) & 0x3FFFF) >> 4) | (1ull << 16) | (16ull << 32) | (3ull << 62);
            auto scores = [&](const uint4& q0, const uint4& q1, const uint4& q2, const uint4& q3) {
                wg_fence();
                wgmma32<0>(de, q0, desc, 0); wgmma32<0>(dx, q0, desc + 64, 0);
                wgmma32<0>(de, q1, desc + 128, 1); wgmma32<0>(dx, q1, desc + 192, 1);
                wgmma32<0>(de, q2, desc + 256, 1); wgmma32<0>(dx, q2, desc + 320, 1);
                wgmma32<0>(de, q3, desc + 384, 1);
                wg_commit();
            };
            scores(tq0, tq1, tq2, tq3);
            stsm4t(uba + (s & 3) * 2048, ub.x, ub.y, ub.z, ub.w);
            rbar += 8;
            pp = g_ACC + (roff - rdelta);
            roff = (roff + ((s & 1) ? 128 : 16384 - 128)) & 65535;
            if (s < NSEG - 1) mbar_wait_nf(bar + B_KV + 8);
            wg_wait0();
#pragma unroll
            for (int r = 0; r < 4; r++) {
                sts32f(smt + (R_SXI - R_SMI) + r * 1024, de[4 * r] + dx[4 * r + 2]); sts32f(smt + (R_SXI - R_SMI) + r * 1024 + 32, de[4 * r + 1] + dx[4 * r + 3]);
            }
            bar_arrive<BR, 256>();
            {
                uint8_t* redp = (uint8_t*)pp + rdelta;
                if (__any_sync(0xffffffffu, bad)) {
                    float e[8];
#pragma unroll
                    for (int i = 0; i < 8; i++) e[i] = lds32f(sb + R_SMX + (i >> 1) * 256 + (i & 1) * 32 + ((l8 & 24) << 3) + ((l8 >> 3) & 28));
                    float m = fmaxf(d0, d1);
#pragma unroll
                    for (int i = 0; i < 8; i++) m = fmaxf(m, e[i]);
                    m = fmaxf(m, __shfl_xor_sync(0xffffffffu, m, 1)); m = fmaxf(m, __shfl_xor_sync(0xffffffffu, m, 2));
#pragma unroll
                    for (int i = 0; i < 8; i++) e[i] = ex2(e[i] - m);
                    const uint32_t pn = pack(ex2(d0 - m), ex2(d1 - m));
                    const uint4 ea = make_uint4(pack(e[0], e[1]), 0u, pack(e[2], e[3]), 0u), eb = make_uint4(pack(e[4], e[5]), 0u, pack(e[6], e[7]), 0u);
                    const uint4 u4 = ldsm4t(uba + (s & 3) * 2048);
                    const uint32_t uq[4] = {u4.x, u4.y, u4.z, u4.w};
#pragma unroll
                    for (int q = 0; q < 4; q++) {
                        const uint4 vb = ldsm4t(lw - w * 3584 + R_STG + S_V + stg + (q < 2 ? tl0 + q : (q == 2 ? tl2 : tl3)) * 512);
                        mmaz(o[q], ea, vb.x, vb.y); mma(o[q], eb, vb.z, vb.w); mma8(o[q], pn, 0u, uq[q]);
                    }
                    mmaz(o[4], ea, ONE2, ONE2); mma(o[4], eb, ONE2, ONE2); mma8(o[4], pn, 0u, ONE2);
                    const float r2 = rcp(o[4][0]);
                    if (bad) red_bf16x8(redp, pack(o[0][0] * r2, o[0][1] * r2), pack(o[1][0] * r2, o[1][1] * r2), pack(o[2][0] * r2, o[2][1] * r2),
                                        __byte_perm(pack(o[3][0] * r2, o[3][1] * r2), CNT1, psel));
                    __syncwarp();
                }
            }
            { const uint32_t ds = stg == (NST - 1) * STGB ? -(NST - 1) * STGB : STGB; stg += ds; vaA += ds; vaB += ds; kq += ds; }
            DBG(9);
            while ((int)(clk() - t0) < POLL_DELAY) {}
            v0 = ld_poll(pp); v1 = ld_poll(pp + 3 * 4096); v2 = ld_poll(pp + 4096); v3 = ld_poll(pp + 2 * 4096);
            bar_arrive<BL, 160>();
            FENCE();
            bar_sync<BS, 128>();
            {
                const uint32_t a = l8 + R_SXI + w * 1024, rw = mapa(sb, w);
                const float2 p0 = lds64f(a), p1 = lds64f(a + 256), p2 = lds64f(a + 512), p3 = lds64f(a + 768);
                sta2f(l8 + (rw - sb + R_LX + (s & 1) * 1024 + c * 256), rw + R_BAR + B_L1 + s * 8, (p0.x + p1.x) + (p2.x + p3.x), (p0.y + p1.y) + (p2.y + p3.y));
            }
            if (w == 3 && s < NSEG - 1) {
                if (elect()) tma2d(sb + R_BK, &maps.acc, ((s + 1) & 1) * 16, (((s + 1) >> 1) & 3) * 64, bar + B_BK + 8);
                __syncwarp();
            }
        }
        if (tid == 0) GT(0, 3);
        mbar_wait_nf(sb + R_BAR + B_BK + (NSEG - 1) * 8);
        asm volatile("cp.async.wait_all;" ::: "memory");
    } else {
        const int* flagp = g_FLAG + (lane == 2 ? 32 + 2 * h + (c >> 1) : 2 * h + (lane & 1)) * 64;
        if (w == 1) {
            asm volatile("fence.proxy.async.shared::cta;" ::: "memory");
            wait_flag(flagp, 4);
            asm volatile("fence.proxy.async.global;" ::: "memory");
            if (elect()) { load_stage(sb, 0, 0, h, c, &maps.x); load_stage(sb, 1, STGB, h, c, &maps.x); }
            __syncwarp();
        }
        if (w == 2) wait_flag(&g_FLAG[F_XA * 32], 192);
        uint32_t pr[5];
        auto softmax = [&](int s, uint32_t stg) {
            const uint32_t a = l8 + R_LX + (s & 1) * 1024, x = l16 + R_STG + stg + S_XX;
            const float4 q0 = lds128f(x), q1 = lds128f(x + 1024), q2 = lds128f(x + 512), q3 = lds128f(x + 1536);
            const float2 p0 = lds64f(a), p1 = lds64f(a + 256), p2 = lds64f(a + 512), p3 = lds64f(a + 768);
            float v[10] = {q0.x + q1.x, q0.y + q1.y, q0.z + q1.z, q0.w + q1.w, q2.x + q3.x, q2.y + q3.y, q2.z + q3.z, q2.w + q3.w,
                           (p0.x + p1.x) + (p2.x + p3.x), (p0.y + p1.y) + (p2.y + p3.y)};
            const int lim = 8 * c + g - 2 * t;
#pragma unroll
            for (int i = 0; i < 8; i++) v[i] = (8 * (i >> 1) + (i & 1) <= lim) ? v[i] : -INFINITY;
            float m = fmaxf(fmaxf(fmaxf(fmaxf(v[0], v[1]), fmaxf(v[2], v[3])), fmaxf(fmaxf(v[4], v[5]), fmaxf(v[6], v[7]))), fmaxf(v[8], v[9]));
            m = fmaxf(m, __shfl_xor_sync(0xffffffffu, m, 1)); m = fmaxf(m, __shfl_xor_sync(0xffffffffu, m, 2));
            float l = 0.f;
#pragma unroll
            for (int i = 0; i < 10; i++) { v[i] = ex2(v[i] - m); l += v[i]; }
            l += __shfl_xor_sync(0xffffffffu, l, 1); l += __shfl_xor_sync(0xffffffffu, l, 2);
            const float r = rcp(l);
#pragma unroll
            for (int q = 0; q < 5; q++) pr[q] = pack(v[2 * q] * r, v[2 * q + 1] * r);
        };
        auto send_p = [&](int s) {
            const uint32_t r0 = mapa(sb, 0), rstride = mapa(sb, 1) - r0;
            const uint32_t a = r0 + R_PB + (s & 3) * 2176, b = r0 + R_BAR + B_L2 + s * 8;
#pragma unroll
            for (int q = 0; q < 4; q++) sta4(a + q * rstride + c * 512 + lane * 16, b + q * rstride, pr[4], pr[0], pr[1], pr[2]);
            if (c == 3) {
#pragma unroll
                for (int q = 0; q < 4; q++) sta1(a + q * rstride + 2048 + lane * 4, b + q * rstride, pr[3]);
            }
        };
        auto pv = [&](int s, uint32_t stg, int m0, bool third) {
            const uint32_t pa = R_PB + (s & 3) * 2176;
            const uint32_t va = sb + R_STG + stg + S_V + (lane & 7) * 16 + (lane & 8) * 64 + m0 * 1024, vb = va + 128 + (lane >> 4) * 128;
            const uint32_t ua = lane < 16 ? l16 + R_UB + (s & 3) * 2048 + m0 * 256 : va, ud = lane < 16 ? 256 : 1024;
            const uint32_t oa = sb + R_OUT + (s & 1) * 7168 + ((lane & 7) + (lane >> 4) * 8) * (OWIDE ? 224 : 112);
            const int ot = 2 * m0 + ((lane >> 3) & 1);
            auto oaddr = [&](int tl) { return oa + tl * 16 + (!OWIDE && tl >= 7 ? 3584 - 112 : 0); };
            const uint4 a0 = ldsm4t(ua), p3 = lds128(l16 + pa + 1536), p2 = lds128(l16 + pa + 1024), a1 = ldsm4t(vb), p1 = lds128(l16 + pa + 512);
            const uint2 p0 = lds64(l16 + pa);
            const uint4 a2 = ldsm4t(va + 384 + (lane >> 4) * 1024);
            const uint32_t p4 = lds32(sb + pa + 2048 + lane * 4);
            const uint4 b0 = ldsm4t(ua + ud), b1 = ldsm4t(vb + 1024);
            FENCE();
            auto tile = [&](const uint4& q0, const uint4& q1, uint32_t q2, uint32_t q3, uint32_t o) {
                float x[4][4];
                mmaz(x[3], q0, p3.x, p3.y); mmaz(x[2], q0, p2.x, p2.y); mmaz(x[1], q0, p1.x, p1.y); mmaz(x[0], q0, p0.x, p0.y);
                mma(x[3], q1, p3.z, p3.w); mma(x[2], q1, p2.z, p2.w); mma(x[1], q1, p1.z, p1.w);
                mma8(x[3], q2, q3, p4);
                stsm4t(o, pack(x[0][0], x[0][1]), pack(x[0][2], x[0][3]), pack(x[1][0], x[1][1]), pack(x[1][2], x[1][3]));
                stsm4t(o + (OWIDE ? 3584 : 1792), pack(x[2][0], x[2][1]), pack(x[2][2], x[2][3]), pack(x[3][0], x[3][1]), pack(x[3][2], x[3][3]));
            };
            tile(a0, a1, a2.x, a2.y, oaddr(ot));
            if (third) {
                const uint4 c0 = ldsm4t(ua + 2 * ud), c1 = ldsm4t(vb + 2048);
                const uint2 c2 = ldsm2t(va + 384 + 2048);
                tile(b0, b1, a2.z, a2.w, oaddr(ot + 2));
                tile(c0, c1, c2.x, c2.y, oaddr(ot + 4));
            } else tile(b0, b1, a2.z, a2.w, oaddr(ot + 2));
        };
        const uint32_t ba = lw + R_MB, upa = l8 + R_UP + w * 1024;
        const uint32_t rdst = opq(rsb + R_SMX + c * 256 + lane * 8), edst = opq(rsb + R_SME + c * 128 + lane * 4);
        uint32_t rbar = opq(rsb + R_BAR + B_SM + (lw & 15)), ebar = opq(rsb + R_BAR + B_SX + (lw & 15));
        uint32_t stg2 = 2 * STGB, stgv = (NST - 2) * STGB;
#pragma unroll 1
        for (int s = 0; s < NSEG; s++) {
            uint4 w0[7];
#pragma unroll
            for (int m = 0; m < 7; m++) w0[m] = lds128v(lw + R_W0 + 14336 + m * 512);
            bar_sync<BX, 256>();
            const float2 p0 = lds64f(l8 + R_SXJ), p1 = lds64f(l8 + R_SXJ + 256), p2 = lds64f(l8 + R_SXJ + 512), p3 = lds64f(l8 + R_SXJ + 768);
            FENCE();
            const uint4 v0 = ldsm4(ba), v1 = ldsm4(ba + 512), v2 = ldsm4(ba + 1024);
            const uint2 v3 = ldsm2(ba + 1536);
            FENCE();
            {
                const float s0 = (p0.x + p1.x) + (p2.x + p3.x), s1 = (p0.y + p1.y) + (p2.y + p3.y);
                sta1(edst, ebar, pack(ex2(s0), ex2(s1)));
                sta2f(rdst, rbar, s0, s1);
            }
            DBG(21);
            float acc[7][4];
            const uint32_t b[14] = {v0.x, v0.y, v0.z, v0.w, v1.x, v1.y, v1.z, v1.w, v2.x, v2.y, v2.z, v2.w, v3.x, v3.y};
            bar_sync<BH, 256>();
            FENCE();
#pragma unroll
            for (int j = 0; j < 3; j++) { A(0, j); FENCE(); A(1, j); FENCE(); A(2, j); if (j < 2) FENCE(); }
            bar_sync<BG, 256>();
            FENCE();
            DBG(20);
            A(0, 3); A(1, 3); FENCE(); A(2, 3); A(3, 0); FENCE();
            A(0, 4); A(1, 4); FENCE(); A(2, 4); A(4, 0); FENCE();
            A(0, 5); A(1, 5); FENCE(); A(2, 5); A(5, 0); FENCE();
            A(0, 6); A(1, 6); FENCE(); A(2, 6); A(6, 0); FENCE();
            A(3, 1); A(4, 1); FENCE();
            A(5, 1); A(6, 1); sts64(upa, pack(acc[0][0], acc[0][1]), pack(acc[0][2], acc[0][3])); FENCE();
            A(3, 2); A(4, 2); sts64(upa + 256, pack(acc[1][0], acc[1][1]), pack(acc[0][2], acc[0][3])); sts64(upa + 512, pack(acc[2][0], acc[2][1]), pack(acc[2][2], acc[2][3])); FENCE();
            A(5, 2); A(6, 2); sts64(upa + 768, pack(acc[1][2], acc[1][3]), pack(acc[2][2], acc[2][3]));
            bar_arrive<BV, 256>(); FENCE();
#pragma unroll
            for (int j = 3; j < 7; j++) { A(3, j); A(4, j); A(5, j); A(6, j); FENCE(); }
#pragma unroll
            for (int m = 3; m < 7; m++) { sts64(upa + 4096 + (m - 3) * 256, pack(acc[m][0], acc[m][1]), pack(acc[m][2], acc[m][3])); if (m == 4) FENCE(); }
            bar_arrive<BU, 256>();
            DBG(22);
            if (w == 0) {
                if (s > 0) mbar_wait(sb + R_BAR + B_L1 + (s - 1) * 8, 0);
                bar_sync<BR, 256>();
                if (s > 0) { softmax(s - 1, stgv == (NST - 1) * STGB ? 0 : stgv + STGB); send_p(s - 1); }
            } else {
                if (s > 1) mbar_wait(sb + R_BAR + B_L2 + (s - 2) * 8, 0);
                int have = 0;
                const int* fp = flagp + ((s + 2) & 2) * 16;
                if (w == 1) {
                    asm volatile("cp.async.bulk.wait_group.read 0;" ::: "memory");
                    asm volatile("fence.proxy.async.shared::cta;" ::: "memory");
                    if (s > 0) mbar_wait_nf(sb + R_BAR + B_BK + s * 8);
                    if (!(s & 1)) have = ld_flag(fp);
                }
                if (w == 2 && blockIdx.x == 0 && lane == 0 && s <= NSEG - RING) st_flag(&g_FLAG[F_PROG * 32], s);
                bar_sync<BR, 256>();
                if (s > 1) pv(s - 2, stgv, 2 * w - 2, w == 3);
                if (w == 2) {
                    if (lane < 28 && s + 4 < NSEG) *((uint4*)(out + (size_t)(32 * s + 128 + (blockIdx.x >> 1)) * OUTW + D) + (blockIdx.x & 1) * 28 + lane) = make_uint4(0, 0, 0, 0);
                    if (lane < 8 && s > 1) *(uint4*)(g_ACC + (((s - 2) >> 1) & 3) * 16384 + (s & 1) * 128 + blockIdx.x * 256 + lane * 16) = make_uint4(0, 0, 0, 0);
                    __syncwarp();
                    if (s == NSEG - 1) retire(total);
                }
                if (w == 1) {
                    if (!(s & 1) && s + 2 < NSEG) {
                        if (__any_sync(0xffffffffu, have < ((s + 2) | 3) + 1)) wait_flag(fp, ((s + 2) | 3) + 1);
                        asm volatile("fence.proxy.async.global;" ::: "memory");
                    }
                    bar_sync<BL, 160>();
                    FENCE();
                    const uint32_t t1 = clk(); while ((int)(clk() - t1) < TMA_DELAY) {}
                    if (elect()) {
                        if (s + 2 < NSEG) load_stage(sb, s + 2, stg2, h, c, &maps.x);
                        if (s > 2) tma_red2d(&maps.out, OWIDE ? 4 + c : 8 + 2 * c, 32 * (s - 3), sb + R_OUT + ((s - 3) & 1) * 7168);
                    }
                    __syncwarp();
                }
            }
            DBG(24);
            stg2 = stg2 == (NST - 1) * STGB ? 0 : stg2 + STGB;
            stgv = stgv == (NST - 1) * STGB ? 0 : stgv + STGB;
            rbar += 8; ebar += 8;
        }
        if (w == 0) { mbar_wait(sb + R_BAR + B_L1 + (NSEG - 1) * 8, 0); softmax(NSEG - 1, ((NSEG - 1) % NST) * STGB); send_p(NSEG - 1); }
#pragma unroll 1
        for (int s = NSEG - 3; s < NSEG; s++) {
            if (s > NSEG - 3 && w > 0) { mbar_wait(sb + R_BAR + B_L2 + s * 8, 0); pv(s, (s % NST) * STGB, 2 * w - 2, w == 3); }
            asm volatile("fence.proxy.async.shared::cta;" ::: "memory");
            if (w == 1) asm volatile("cp.async.bulk.wait_group.read 0;" ::: "memory");
            bar_sync<BO, 128>();
            if (w == 1 && elect()) tma_red2d(&maps.out, OWIDE ? 4 + c : 8 + 2 * c, 32 * s, sb + R_OUT + (s & 1) * 7168);
            __syncwarp();
        }
        if (w == 1) asm volatile("cp.async.bulk.wait_group 0;" ::: "memory");
        if (tid == 160) GT(0, 4);
    }
    asm volatile("barrier.cluster.arrive.relaxed.aligned; barrier.cluster.wait.aligned;" ::: "memory");
}

constexpr int G_BAR = 229376;
constexpr int G_SMEM = G_BAR + 64;

#define HANDK 13
#define PACE 500
#define STAG 100
#define COVER 7
__device__ __forceinline__ void proj_role(uint32_t sb, const Maps& maps) {
    const int tid = threadIdx.x, lane = tid & 31, wid = __shfl_sync(0xffffffffu, tid >> 5, 0), wg = wid >> 2, u = wid & 3;
    const int g = lane >> 2, t = lane & 3, mt = u & 1;
    const int n = blockIdx.x, M = n >> 5, h = (n >> 1) & 15, hf = n & 1;
    const uint32_t img = sb + (1 - hf) * 28672, own = sb + (1 - hf) * 114688, stg = sb + hf * 200704;
    const int last = hf ? 2 - 2 * wg : 4 + 2 * wg;
    fold(img, hf ? own + 81920 : own, hf ? -32768 : 32768, sb + hf * 114688, sb + G_BAR, n, 4, hf ? 0x0231 : 0x6435, maps, []() {});
    uint4 a[28];
    const uint4* xp = g_XA + wid * 896 + lane;
    const int k0 = 14 * (1 - hf), k1 = 14 * hf;
    auto load = [&](int j0, const uint4* p) {
#pragma unroll
        for (int j = 0; j < 14; j++) a[j0 + j] = ldcg(p + j * 32);
    };
    if (wg == 1) bar_arrive(3, 256);
    if (wg == 1) { fold_done(n, last); mbar_wait_nf(sb + G_BAR + 48); }
    GF(1, 2);
    load(0, xp + k0 * 32); load(14, xp + k1 * 32);
    GF(1, 3);
    if (wid == 3) {
        wait_flag(g_FLAG + (F_IMG + n) * 32 + 4 * hf + min(lane, 2), 2);
        bar_sync<9, 160>();
        if (elect()) {
            asm volatile("fence.proxy.async.global;" ::: "memory");
            GE(1, 26);
            mbar_expect(sb + G_BAR + 48, 86016);
            bulk_g2s(img + hf * 114688, g_FI + (size_t)n * 200704 + hf * 114688, 86016, sb + G_BAR + 48);
        }
        __syncwarp();
    }
    if (wg == 0) { fold_done(n, last); bar_sync(3, 256); }
    if (tid == 0) GT(1, 1);
    const uint64_t desc0 = mdesc(img + k0 * 7168, 512, 3584, 2), desc1 = mdesc(img + k1 * 7168, 512, 3584, 2);
    int prog = 0;
#pragma unroll 1
    for (int it = 0; it < 16; it++) {
        const int seg = 4 * it + 2 * wg + (u >> 1);
        float d[112];
        if (it > 0 || wg == 1) bar_sync(1 + wg, 256);
        wg_fence();
#pragma unroll
        for (int j = 0; j < 14; j++) wgmma224<1>(d, a[j], desc0 + j * (7168 >> 4), j);
        wg_commit();
        if (it == 0) { GF(1, 6); mbar_wait_nf(sb + G_BAR + 48); GF(1, 7); }
        wg_fence();
#pragma unroll
        for (int j = 0; j < COVER; j++) wgmma224<1>(d, a[14 + j], desc1 + j * (7168 >> 4), true);
        wg_commit();
        const bool more = it < 15, other = M == 0 && mt == 0;
        wg_wait<1>();
        load(0, xp + (other ? 896 + k1 * 32 : (more ? 8 * 896 : 0) + k0 * 32));
        xp += more ? 8 * 896 : 0;
        wg_fence();
#pragma unroll
        for (int j = COVER; j < 14; j++) wgmma224<1>(d, a[14 + j], desc1 + j * (7168 >> 4), true);
        wg_commit();
        if (M == 1 && (wg == 0 || more)) bar_arrive(2 - wg, 256);
        const int ri = ((seg % RING) * 16 + h) * 4;
        wg_wait<0>();
        if (it == 0 && tid == 0) GE(1, 27);
        uint4 lo[7], hi[7];
#pragma unroll
        for (int q = 0; q < 7; q++) {
            const float* e = d + 16 * q;
            lo[q] = make_uint4(pack(e[0], e[1]), pack(e[4], e[5]), pack(e[8], e[9]), pack(e[12], e[13]));
            hi[q] = make_uint4(pack(e[2], e[3]), pack(e[6], e[7]), pack(e[10], e[11]), pack(e[14], e[15]));
        }
        float s0[4], s1[4], s2[4], s3[4];
        if (M == 0) {
            if (mt == 0) {
#pragma unroll
                for (int k = 0; k < 14; k++) {
                    const uint32_t l0 = (k & 1) ? lo[k >> 1].z : lo[k >> 1].x, l1 = (k & 1) ? lo[k >> 1].w : lo[k >> 1].y;
                    const uint32_t h0 = (k & 1) ? hi[k >> 1].z : hi[k >> 1].x, h1 = (k & 1) ? hi[k >> 1].w : hi[k >> 1].y;
                    if (k == 0) { mmaz(s0, a[14], l0, l1); mmaz(s1, a[14], h0, h1); mmaz(s2, a[0], l0, l1); mmaz(s3, a[0], h0, h1); }
                    else { mma(s0, a[14 + k], l0, l1); mma(s1, a[14 + k], h0, h1); mma(s2, a[k], l0, l1); mma(s3, a[k], h0, h1); }
                    if (k == HANDK) { FENCE(); if (wg == 0 || more) bar_arrive(2 - wg, 256); FENCE(); }
                }
            } else {
#pragma unroll
                for (int q = 0; q < 7; q++) {
                    const uint4 &a0 = a[14 + 2 * q], &a1 = a[15 + 2 * q];
                    if (q == 0) { mmaz(s0, a0, lo[q].x, lo[q].y); mmaz(s1, a0, hi[q].x, hi[q].y); mmaz(s2, a1, lo[q].z, lo[q].w); mmaz(s3, a1, hi[q].z, hi[q].w); }
                    else { mma(s0, a0, lo[q].x, lo[q].y); mma(s1, a0, hi[q].x, hi[q].y); mma(s2, a1, lo[q].z, lo[q].w); mma(s3, a1, hi[q].z, hi[q].w); }
                }
#pragma unroll
                for (int i = 0; i < 4; i++) { s2[i] += s0[i]; s3[i] += s1[i]; }
                FENCE();
                if (wg == 0 || more) bar_arrive(2 - wg, 256);
            }
        }
        if (it > 0 || wg == 1) bar_sync(4 + wg, 256);
        const int l2 = (int)(xp - g_XA) & 31;
        const uint32_t st0 = stg + u * 7168 + (l2 & 3) * 256 + (((l2 >> 2) ^ (2 * (l2 & 3))) << 4), st1 = (st0 + 128) ^ 16;
#pragma unroll
        for (int q = 0; q < 7; q++) { sts128(st0 + q * 1024, lo[q]); sts128(st1 + q * 1024, hi[q]); }
        asm volatile("fence.proxy.async.shared::cta;" ::: "memory");
        __syncwarp();
        const uint32_t ts = clk();
        if (it == 0 && tid == 0) GE(1, 28);
        int back = 0;
        if (M == 0) {
            float4* sp = (float4*)(g_REC + (size_t)ri * RECC + S_XX + hf * 1024 + mt * 512) + l2;
            sp[2 * RECC / 16] = make_float4(s2[0], s2[1], s3[0], s3[1]); sp[3 * RECC / 16] = make_float4(s2[2], s2[3], s3[2], s3[3]);
            if (mt == 0) {
                sp[0] = make_float4(s0[0], s0[1], s1[0], s1[1]); sp[RECC / 16] = make_float4(s0[2], s0[3], s1[2], s1[3]);
                back = ld_flag((const int*)sp) ^ ld_flag((const int*)(sp + RECC / 16));
                load(0, xp + k0 * 32);
            }
            back ^= ld_flag((const int*)(sp + 2 * RECC / 16)) ^ ld_flag((const int*)(sp + 3 * RECC / 16));
        }
        FENCE();
        load(14, xp + k1 * 32);
        FENCE();
        if (it > 0) while ((int)(clk() - ts) < ((u + n) & 3) * PACE) {}
        if (elect()) {
            if (M == 0) asm volatile("cp.async.bulk.tensor.3d.global.shared::cta.tile.bulk_group [%0,{%1,%2,%3}],[%4];"
                                     ::"l"(&maps.rk), "r"(0), "r"(ri + 2 * mt), "r"(28 * hf), "r"(stg + u * 7168) : "memory");
            else asm volatile("cp.async.bulk.tensor.4d.global.shared::cta.tile.bulk_group [%0,{%1,%2,%3,%4}],[%5];"
                              ::"l"(&maps.rv), "r"(0), "r"(2 * mt), "r"(0), "r"(ri + 2 * hf), "r"(stg + u * 7168) : "memory");
            asm volatile("cp.async.bulk.commit_group;" ::: "memory");
        }
        __syncwarp();
        asm volatile("cp.async.bulk.wait_group.read 0;" ::: "memory");
        if (wg == 0 || more) bar_arrive(5 - wg, 256);
        back = __reduce_or_sync(0xffffffffu, (unsigned)back);
        if (elect()) {
            asm volatile("cp.async.bulk.wait_group 0; fence.proxy.async.global;" ::: "memory");
            asm volatile("red.relaxed.gpu.global.add.s32 [%0],%1;" ::"l"(g_FLAG + (n * 2 + wg) * 32), "r"(1 + (back & (int)(blockDim.y - 1))) : "memory");
        }
        __syncwarp();
        if (tid == 32 && it == 0) GT(1, 2);
        if (u == 3 && more) {
            int i2 = 0;
            while (prog < max(seg + 5 - RING, seg + 4 >= ALIAS ? 1 : 0)) { if (i2) __nanosleep(400); prog = __shfl_sync(0xffffffffu, ld_flag(&g_FLAG[F_PROG * 32]), 0); if (++i2 > (1 << 18)) __trap(); }
            if (i2 > 1) __nanosleep((n & 15) * STAG);
        }
    }
}

struct PartA { const __nv_bfloat16 *lar, *aim, *cre, *cim, *ldt, *dsk; };
constexpr int C_PP = 4368, C_TP = 272, C_TW = 56 * C_TP;
constexpr int C_RAW = 0;
constexpr int C_PL = 65536;
constexpr int C_T = C_PL + 8 * C_PP;
constexpr int C_KS = 8320;
constexpr int C_BAR = C_T + 8 * C_TW, C_UNIT = C_BAR + 16;
static_assert(C_UNIT + 8 <= G_SMEM, "conv smem");

#define AHEAD 12
struct cpx { float r, i; };
__device__ __forceinline__ cpx cmul(cpx a, cpx b) { return {fmaf(a.r, b.r, -a.i * b.i), fmaf(a.r, b.i, a.i * b.r)}; }
__device__ __forceinline__ cpx cmulc(cpx a, cpx b) { return {fmaf(a.r, b.r, a.i * b.i), fmaf(a.i, b.r, -a.r * b.i)}; }
__device__ __forceinline__ cpx cexp(float er, float wi, float p) {
    const float e = ex2(er * p), x = wi * p;
    const float k = rintf(x * 0.15915494309189535f);
    const float r = fmaf(k, 1.7484555314695172e-07f, fmaf(k, -6.2831854820251465f, x));
    return {e * __cosf(r), e * __sinf(r)};
}
__device__ __forceinline__ uint32_t lds16(uint32_t a) { uint32_t k; asm volatile("{.reg .u16 h; ld.shared.u16 h,[%1]; cvt.u32.u16 %0,h;}" : "=r"(k) : "r"(a) : "memory"); return k; }
__device__ __forceinline__ float rbf(float x) { return __bfloat162float(__float2bfloat16(x)); }

__device__ __forceinline__ void kgen(uint32_t tb, uint4 la, uint4 ai, uint4 cr, uint4 ci, float ldt) {
    const int lane = threadIdx.x & 31, g = lane >> 2, t = lane & 3;
    const float dt = rbf(expf(ldt));
    float acc[2][3][4];
#pragma unroll
    for (int i = 0; i < 6; i++) acc[i / 3][i % 3][0] = acc[i / 3][i % 3][1] = acc[i / 3][i % 3][2] = acc[i / 3][i % 3][3] = 0.f;
    const uint32_t wa = tb + lane * 8, ra = tb + (lane & 15) * C_TP + (lane >> 4) * 16, rb = tb + (32 + (lane & 7)) * C_TP + (lane >> 3) * 16;
#pragma unroll 1
    for (int it = 0; it < 4; it++) {
        cpx c[2], w1[2], w2[2], w4[2], w8[2], w256[2], y[2][4];
#pragma unroll
        for (int z = 0; z < 2; z++) {
            auto half = [&](uint32_t v) { return __uint_as_float(z ? v & 0xffff0000u : v << 16); };
            const float er = (-rbf(expf(half(la.x))) * dt) * LOG2E, wi = half(ai.x) * dt;
            c[z] = {2.f * (half(cr.x) * dt), -2.f * (half(ci.x) * dt)};
            w1[z] = cexp(er, wi, 1.f); y[z][1] = cexp(er, wi, 64.f);
            w2[z] = cmul(w1[z], w1[z]); w4[z] = cmul(w2[z], w2[z]); w8[z] = cmul(w4[z], w4[z]);
            y[z][0] = {1.f, 0.f}; y[z][2] = cmul(y[z][1], y[z][1]); y[z][3] = cmul(y[z][2], y[z][1]); w256[z] = cmul(y[z][2], y[z][2]);
        }
        la = make_uint4(la.y, la.z, la.w, 0); ai = make_uint4(ai.y, ai.z, ai.w, 0); cr = make_uint4(cr.y, cr.z, cr.w, 0); ci = make_uint4(ci.y, ci.z, ci.w, 0);
        __syncwarp();
        auto put = [&](int row, cpx a, cpx b) { sts64(wa + row * C_TP, pack(a.r, a.i), pack(b.r, b.i)); };
#pragma unroll
        for (int k = 0; k < 8; k++)
#pragma unroll
            for (int j = 0; j < 4; j++) {
                put(8 * j + k, y[0][j], y[1][j]);
                if (k < 7) { y[0][j] = (k == 0 && j == 0) ? w8[0] : cmul(y[0][j], w8[0]); y[1][j] = (k == 0 && j == 0) ? w8[1] : cmul(y[1][j], w8[1]); }
            }
        cpx x0 = c[0], x1 = c[1], z0 = c[0], z1 = c[1];
        put(32, x0, x1);
#pragma unroll
        for (int k = 1; k < 9; k++) {
            if (k < 8) { x0 = cmulc(x0, w1[0]); x1 = cmulc(x1, w1[1]); put(32 + k, x0, x1); }
            z0 = cmulc(z0, w256[0]); z1 = cmulc(z1, w256[1]);
            put(k == 1 ? 40 : (k < 4 ? 40 + 2 * k : 44 + k), z0, z1);
            if (k == 1) {
                const cpx p0 = cmulc(z0, w4[0]), p1 = cmulc(z1, w4[1]);
                put(41, cmulc(z0, w2[0]), cmulc(z1, w2[1])); put(42, p0, p1); put(43, cmulc(p0, w2[0]), cmulc(p1, w2[1]));
            } else if (k < 4) put(41 + 2 * k, cmulc(z0, w4[0]), cmulc(z1, w4[1]));
        }
        __syncwarp();
#pragma unroll
        for (int kp = 0; kp < 4; kp++) {
            const uint4 b0 = ldsm4(rb + kp * 64), b1 = ldsm4(rb + 8 * C_TP + kp * 64), b2 = ldsm4(rb + 16 * C_TP + kp * 64);
#pragma unroll
            for (int m = 0; m < 2; m++) {
                const uint4 a0 = ldsm4(ra + m * 16 * C_TP + kp * 64), a1 = ldsm4(ra + m * 16 * C_TP + kp * 64 + 32);
                mma(acc[m][0], a0, b0.x, b0.y); mma(acc[m][1], a0, b1.x, b1.y); mma(acc[m][2], a0, b2.x, b2.y);
                mma(acc[m][0], a1, b0.z, b0.w); mma(acc[m][1], a1, b1.z, b1.w); mma(acc[m][2], a1, b2.z, b2.w);
            }
        }
    }
    __syncwarp();
    const uint32_t ks = tb + C_KS;
    const int o1 = t < 2 ? 256 + 4 * t : 256 * t, e1 = t < 2 ? 2 : 4;
#pragma unroll
    for (int q = 0; q < 4; q++) {
        const uint32_t a = ks + 16 * (8 * q + g);
        const float* v0 = acc[q >> 1][0] + 2 * (q & 1); const float* v1 = acc[q >> 1][1] + 2 * (q & 1); const float* v2 = acc[q >> 1][2] + 2 * (q & 1);
        const uint32_t p1 = pack(v1[0], v1[1]), p2 = pack(v2[0], v2[1]);
        sts32(a + 4 * t, pack(v0[0], v0[1]));
        asm volatile("st.shared.u16 [%0],%1;" ::"r"(a + 2 * o1), "h"((uint16_t)p1) : "memory");
        asm volatile("st.shared.u16 [%0],%1;" ::"r"(a + 2 * (o1 + e1)), "h"((uint16_t)(p1 >> 16)) : "memory");
        if (t < 3) asm volatile("st.shared.u16 [%0],%1;" ::"r"(a + 2048 + 1024 * t), "h"((uint16_t)p2) : "memory");
        if (t < 2) asm volatile("st.shared.u16 [%0],%1;" ::"r"(a + 2560 + 1024 * t), "h"((uint16_t)(p2 >> 16)) : "memory");
    }
    __syncwarp();
    auto W = [](uint32_t lo, uint32_t hi) { return __byte_perm(lo, hi, 0x5410); };
    const uint32_t r = tb + 64 + lane * 16, k4 = ks + lane * 8;
    if (lane < 16) sts32(tb + lane * 4, 0u);
#pragma unroll
    for (int i = 0; i < 2; i++) {
        const uint2 v = lds64(k4 + i * 256);
        const uint32_t pv = (lane || i) ? lds32(k4 + i * 256 - 4) : 0u;
        sts128(r + i * 512, __byte_perm(v.x, pv, 0x7610), __byte_perm(v.x, 0, 0x1032), __byte_perm(v.y, v.x, 0x7610), __byte_perm(v.y, 0, 0x1032));
    }
#pragma unroll
    for (int i = 2; i < 4; i++) {
        const uint2 v = lds64(k4 + i * 256);
        const uint32_t c4 = lds32(k4 + i * 256 + 8), pv = (lane || i == 3) ? v.x : lds16(ks + 510);
        sts128(r + i * 512, W(v.x, pv), W(v.x, v.x), W(v.y, v.x), W(c4, v.y));
    }
    {
        const uint32_t s2 = (lane & 1) ? 0x5410u : 0x5454u, s3 = (lane & 1) ? 0x1010u : 0x5410u;
#pragma unroll
        for (int i = 4; i < 8; i++) {
            const uint32_t c0 = lds32(k4 + i * 256), c4 = lds32(k4 + i * 256 + 8);
            sts128(r + i * 512, W(c0, c0), W(c0, c0), __byte_perm(c4, c0, s2), __byte_perm(c4, c0, s3));
        }
    }
    {
        const uint32_t s0 = (lane & 3) == 3 ? 0x5410u : 0x5454u, s1 = (lane & 1) ? ((lane & 2) ? 0x1010u : 0x5410u) : 0x5454u, s2 = (lane & 1) ? 0x1010u : 0x5454u;
        const uint32_t k8 = ks + (lane >> 1) * 16;
#pragma unroll
        for (int i = 8; i < 16; i++) {
            const uint32_t c0 = lds32(k8 + i * 256), c8 = lds32(k8 + i * 256 + 16), w2 = __byte_perm(c8, c0, s2);
            sts128(r + i * 512, __byte_perm(c8, c0, s0), __byte_perm(c8, c0, s1), w2, w2);
        }
    }
}

__device__ __forceinline__ void stsm4(uint32_t a, const uint4& v) {
    asm volatile("stmatrix.sync.aligned.m8n8.x4.shared.b16 [%0],{%1,%2,%3,%4};" ::"r"(a), "r"(v.x), "r"(v.y), "r"(v.z), "r"(v.w) : "memory");
}
__device__ __forceinline__ uint32_t hmul(uint32_t a, uint32_t b) { uint32_t r; asm("mul.rn.bf16x2 %0,%1,%2;" : "=r"(r) : "r"(a), "r"(b)); return r; }

__device__ __forceinline__ void conv_role(uint32_t sb, const PartA& A, const Maps& maps, int total) {
    const int tid = threadIdx.x, lane = tid & 31, ch = __shfl_sync(0xffffffffu, tid >> 5, 0);
    const int g = lane >> 2, t = lane & 3;
    int first = 0;
    if (tid == 0) first = atomicAdd(&g_FLAG[F_WORK * 32], 1);
    __syncthreads();
    if (tid == 0) {
        sts32(sb + C_UNIT, (uint32_t)first);
        mbar_init(sb + C_BAR, 8); mbar_init(sb + C_BAR + 8, 8);
        asm volatile("fence.mbarrier_init.release.cluster; fence.proxy.async.shared::cta;" ::: "memory");
    }
    if (lane < 16) sts128(sb + C_PL + ch * C_PP + (lane >> 3) * 2176 + (lane & 7) * 16, 0u, 0u, 0u, 0u);
    const uint32_t raw0 = sb + C_RAW + ch * 4096 + lane * 16;
    const uint32_t pla = sb + C_PL + (lane & 7) * C_PP + ((lane >> 3) & 1) * 2176 + (8 + 16 * ch + (lane >> 4)) * 16;
    const uint32_t own = sb + C_PL + ch * C_PP + ((lane >> 3) & 1) * 2176 + (8 + 8 * (lane >> 4) + (lane & 7)) * 16;
    uint4 la, ai, cr, ci;
    uint32_t dkn; float ldt;
    auto fetch = [&](int unit, int buf) {
        if (elect()) {
            asm volatile("cp.async.bulk.wait_group.read 0;" ::: "memory");
            mbar_expect(sb + C_BAR + buf * 8, 4096);
            tma2d(sb + C_RAW + buf * 32768 + ch * 4096, &maps.u8, 8 * unit, 256 * ch, sb + C_BAR + buf * 8);
        }
        __syncwarp();
        const int d = 8 * unit + ch;
        la = __ldg((const uint4*)(A.lar + d * NST8) + lane); ai = __ldg((const uint4*)(A.aim + d * NST8) + lane);
        cr = __ldg((const uint4*)(A.cre + d * NST8) + lane); ci = __ldg((const uint4*)(A.cim + d * NST8) + lane);
        ldt = __bfloat162float(A.ldt[d]); dkn = __ldg((const uint32_t*)(A.dsk + 8 * unit) + t);
    };
    __syncthreads();
    int unit = (int)lds32(sb + C_UNIT);
    if (tid == 0) GT(1, 5);
    if (unit < D / 8) fetch(unit, 0);
#pragma unroll 1
    for (int round = 0; unit < D / 8; round++) {
        const uint32_t raw = raw0 + (round & 1) * 32768, dk = dkn;
        int next = 0;
        if (tid == 0) next = blockIdx.x >= 64 && unit < AHEAD ? atomicAdd(&g_FLAG[F_WORK * 32], 1) : -1;
        kgen(sb + C_T + ch * C_TW, la, ai, cr, ci, ldt);
        mbar_wait(sb + C_BAR + (round & 1) * 8, (round >> 1) & 1);
        {
            uint4 v[8];
#pragma unroll
            for (int i = 0; i < 8; i++) v[i] = ldsm4t(raw + i * 512);
#pragma unroll
            for (int i = 0; i < 8; i++) stsm4(pla + i * 32, v[i]);
        }
        if (tid == 0) sts32(sb + C_UNIT, (uint32_t)next);
        __syncthreads();
        next = (int)lds32(sb + C_UNIT);
        if (tid == 0) GT(1, 6);
        if (next >= 0 && next < D / 8) fetch(next, (round + 1) & 1);
        float acc[16][4];
#pragma unroll
        for (int i = 0; i < 16; i++) acc[i][0] = acc[i][1] = acc[i][2] = acc[i][3] = 0.f;
        const uint32_t ra0 = sb + C_T + ch * C_TW + 64 + (g - 2 * t) * 4, rb0 = __shfl_sync(0xffffffffu, ra0, lane);
#pragma unroll 1
        for (int jj = 0; jj < 8; jj++) {
            uint4 win[8];
#pragma unroll
            for (int q = 0; q < 8; q++) win[q] = ldsm4(own - jj * 16 + q * 256);
            const uint32_t ra = ra0 + jj * 64, rb = rb0 + jj * 64;
#pragma unroll
            for (int m = 15; m >= 0; m--) {
                const uint4 a = make_uint4(lds32(ra + m * 512), lds32(ra + m * 512 + 32), lds32(ra + m * 512 - 32), lds32(rb + m * 512));
#pragma unroll
                for (int i = m; i < 16; i++) {
                    const uint4& w = win[(i - m) >> 1];
                    if ((i - m) & 1) mma(acc[i], a, w.z, w.w); else mma(acc[i], a, w.x, w.y);
                }
            }
        }
        int late = 0;
        if (tid == 0 && next < 0) late = atomicAdd(&g_FLAG[F_WORK * 32], 1);
        __syncwarp();
#pragma unroll
        for (int q = 0; q < 8; q++)
            stsm4t(own + q * 256, pack(acc[2 * q][0], acc[2 * q][1]), pack(acc[2 * q][2], acc[2 * q][3]), pack(acc[2 * q + 1][0], acc[2 * q + 1][1]), pack(acc[2 * q + 1][2], acc[2 * q + 1][3]));
        if (tid == 0) sts32(sb + C_UNIT + 4, (uint32_t)late);
        __syncthreads();
        {
            uint4 y[8], v[8];
#pragma unroll
            for (int i = 0; i < 8; i++) { y[i] = ldsm4t(pla + i * 32); v[i] = ldsm4(raw + i * 512); }
#pragma unroll
            for (int i = 0; i < 8; i++)
                stsm4(raw + i * 512, make_uint4(hadd(y[i].x, hmul(v[i].x, dk)), hadd(y[i].y, hmul(v[i].y, dk)), hadd(y[i].z, hmul(v[i].z, dk)), hadd(y[i].w, hmul(v[i].w, dk))));
        }
        asm volatile("fence.proxy.async.shared::cta;" ::: "memory");
        __syncwarp();
        if (next < 0) { next = (int)lds32(sb + C_UNIT + 4); if (next < D / 8) fetch(next, (round + 1) & 1); }
        if (elect()) {
            asm volatile("cp.async.bulk.tensor.2d.global.shared::cta.tile.bulk_group [%0,{%1,%2}],[%3];"
                         ::"l"(&maps.o8), "r"(8 * unit), "r"(256 * ch), "r"(sb + C_RAW + (round & 1) * 32768 + ch * 4096) : "memory");
            asm volatile("cp.async.bulk.commit_group;" ::: "memory");
        }
        __syncwarp();
        unit = next;
    }
    if (tid == 0) GT(1, 7);
    if (ch == 0) retire(total);
    asm volatile("cp.async.bulk.wait_group 0;" ::: "memory");
}

__global__ void __launch_bounds__(256, 1)
k_bulk(const PartA A, const __grid_constant__ Maps maps, int total) {
    extern __shared__ __align__(1024) uint8_t smem[];
    const uint32_t sb = smem_u32(smem);
    const int n = blockIdx.x, tid = threadIdx.x;
    if (tid == 0) GT(1, 0);
    asm volatile("prefetch.tensormap [%0];" ::"l"(&maps.k64 + __shfl_sync(0xffffffffu, tid >> 5, 0)) : "memory");
    if (n < 64) proj_role(sb, maps);
    if (tid == 0) GT(1, 3);
    conv_role(sb, A, maps, total);
    if (tid == 0) GT(1, 4);
}

}

#define PROMO P0
extern "C" void kernel_launch(void* const* d_in, const int* in_sizes, int n_in, void* d_out, int out_size) {
    typedef const __nv_bfloat16* P;
    const PartA A = {(P)d_in[1], (P)d_in[2], (P)d_in[3], (P)d_in[4], (P)d_in[5], (P)d_in[6]};
    const P x = (P)d_in[7], mem0 = (P)d_in[8], wq = (P)d_in[9], wk = (P)d_in[10], wv = (P)d_in[11], wo = (P)d_in[12];
    typedef CUresult (*EncodeFn)(CUtensorMap*, CUtensorMapDataType, cuuint32_t, void*, const cuuint64_t*, const cuuint64_t*, const cuuint32_t*,
                                 const cuuint32_t*, CUtensorMapInterleave, CUtensorMapSwizzle, CUtensorMapL2promotion, CUtensorMapFloatOOBfill);
    static EncodeFn encode = nullptr;
    static int nsm = 0;
    constexpr int RS = R_SMEM;
    if (!encode) {
        cudaFuncSetAttribute(k_rec, cudaFuncAttributeMaxDynamicSharedMemorySize, RS);
        cudaFuncSetAttribute(k_bulk, cudaFuncAttributeMaxDynamicSharedMemorySize, G_SMEM);
        if (CLUSTER > 8) cudaFuncSetAttribute(k_rec, cudaFuncAttributeNonPortableClusterSizeAllowed, 1);
        int dev = 0; cudaGetDevice(&dev);
        cudaDeviceGetAttribute(&nsm, cudaDevAttrMultiProcessorCount, dev);
        cudaDriverEntryPointQueryResult qr;
        cudaGetDriverEntryPoint("cuTensorMapEncodeTiled", (void**)&encode, cudaEnableDefault, &qr);
    }
    struct U4 { cuuint64_t v[4]; };
    auto make = [&](CUtensorMap& m, CUtensorMapDataType ty, int rank, const void* p, U4 dims, U4 strides, U4 box, CUtensorMapSwizzle sw, CUtensorMapL2promotion pr) {
        const cuuint32_t b[4] = {(cuuint32_t)box.v[0], (cuuint32_t)box.v[1], (cuuint32_t)box.v[2], (cuuint32_t)box.v[3]}, es[4] = {1, 1, 1, 1};
        encode(&m, ty, rank, (void*)p, dims.v, strides.v, b, es, CU_TENSOR_MAP_INTERLEAVE_NONE, sw, pr, CU_TENSOR_MAP_FLOAT_OOB_FILL_NONE);
    };
    const CUtensorMapDataType BF = CU_TENSOR_MAP_DATA_TYPE_BFLOAT16;
    const CUtensorMapL2promotion P0 = CU_TENSOR_MAP_L2_PROMOTION_NONE, P2 = CU_TENSOR_MAP_L2_PROMOTION_L2_256B;
    void* acc; cudaGetSymbolAddress(&acc, g_ACC);
    Maps maps;
    make(maps.x, BF, 3, x, {16, S, 28}, {D * 2, 32}, {16, 32, 7}, CU_TENSOR_MAP_SWIZZLE_32B, P0);
    if (OWIDE) make(maps.out, BF, 3, d_out, {112, S, 8}, {OUTW * 2, 224}, {112, 32, 1}, CU_TENSOR_MAP_SWIZZLE_NONE, P0);
    else make(maps.out, BF, 3, d_out, {56, S, 16}, {OUTW * 2, 112}, {56, 32, 2}, CU_TENSOR_MAP_SWIZZLE_NONE, P0);
    make(maps.acc, CU_TENSOR_MAP_DATA_TYPE_UINT64, 2, acc, {32, 4 * 64}, {256}, {16, 64}, CU_TENSOR_MAP_SWIZZLE_NONE, P0);
    make(maps.k64, BF, 4, wk, {64, 8, 64, 56}, {8192, 128, 65536}, {64, 8, 4, 8}, CU_TENSOR_MAP_SWIZZLE_128B, PROMO);
    make(maps.v64, BF, 4, wv, {64, 8, 64, 56}, {8192, 128, 65536}, {64, 8, 4, 8}, CU_TENSOR_MAP_SWIZZLE_128B, PROMO);
    make(maps.q224, BF, 4, wq, {64, 8, 64, 56}, {8192, 128, 65536}, {64, 8, QFULL ? 4 : 2, QFULL ? 14 : 28}, CU_TENSOR_MAP_SWIZZLE_128B, PROMO);
    make(maps.o224, BF, 4, wo, {32, 8, 14, 512}, {D * 2, 64, D * 16}, {32, 8, 7, 16}, CU_TENSOR_MAP_SWIZZLE_64B, PROMO);
    make(maps.u8, BF, 2, d_in[0], {D, S}, {D * 2}, {8, 256}, CU_TENSOR_MAP_SWIZZLE_NONE, P0);
    make(maps.o8, BF, 2, d_out, {OUTW, S}, {OUTW * 2}, {8, 256}, CU_TENSOR_MAP_SWIZZLE_NONE, P0);
    void* rec; cudaGetSymbolAddress(&rec, g_REC);
    make(maps.rk, CU_TENSOR_MAP_DATA_TYPE_UINT64, 3, rec, {16, RING * 64, 56}, {RECC, 128}, {16, 2, 28}, CU_TENSOR_MAP_SWIZZLE_128B, P0);
    make(maps.rv, CU_TENSOR_MAP_DATA_TYPE_UINT64, 4, (uint8_t*)rec + S_V, {16, 4, 14, RING * 64}, {128, 512, RECC}, {16, 2, 14, 2}, CU_TENSOR_MAP_SWIZZLE_128B, P0);
    k_rec<<<64, 256, RS, cudaStreamPerThread>>>(mem0, x, (__nv_bfloat16*)d_out, maps, nsm);
    cudaLaunchAttribute pdl[1];
    pdl[0].id = cudaLaunchAttributeProgrammaticStreamSerialization;
    pdl[0].val.programmaticStreamSerializationAllowed = 1;
    cudaLaunchConfig_t cfg = {};
    cfg.stream = cudaStreamPerThread;
    cfg.attrs = pdl; cfg.numAttrs = 1;
    cfg.gridDim = dim3(nsm - 64); cfg.blockDim = dim3(256); cfg.dynamicSmemBytes = G_SMEM;
    cudaLaunchKernelEx(&cfg, k_bulk, A, maps, nsm);
}
```
